```python
import torch

def _softmax(x, axis=-1):
    return torch.softmax(x, dim=axis)
def _gelu(x):
    return torch.nn.functional.gelu(x, approximate="tanh")
def _silu(x):
    return torch.nn.functional.silu(x)
def _sigmoid(x):
    return torch.sigmoid(x)
def _layernorm(x, axis=-1, eps=1e-5):
    m = x.mean(dim=axis, keepdim=True)
    v = x.var(dim=axis, keepdim=True, unbiased=False)
    return (x - m) / torch.sqrt(v + eps)
def _scatter_add(tgt, idx, src, axis=0):
    return tgt.clone().index_add_(axis, idx, src)
def _segment_sum(src, seg, n):
    out = torch.zeros((n,) + src.shape[1:], dtype=src.dtype)
    return out.index_add_(0, seg, src)
def _pad(x, pw):
    flat = tuple(v for pair in reversed(pw) for v in pair)
    return torch.nn.functional.pad(x, flat)

kernel_name = 'parallel_sum__sliding_block_cached__geglu_ffn__decode'

def setup_inputs():

    _w = (lambda a: (lambda t: t.to(torch.bfloat16) if t.is_floating_point() else t)(torch.as_tensor(a)))
    def _A_setup():
        B, Sq, D = 1, 1, 576
        Hq, Hkv, Sk, Dh = 32, 16, 65536, 128
        assert Hq % Hkv == 0, (Hq, Hkv)
        return {
            "x": _w((lambda *s: torch.randn(*s, dtype=torch.bfloat16) * 0.05)(B, Sq, D)),
            "k_cache": _w((lambda *s: torch.randn(*s, dtype=torch.bfloat16) * 3.2)(B, Hkv, Sk, Dh)),
            "v_cache": _w((lambda *s: torch.randn(*s, dtype=torch.bfloat16) * 1.6)(B, Hkv, Sk, Dh)),
            "wq": _w((lambda *s: torch.randn(*s, dtype=torch.bfloat16) * 3.2)(D, Hq * Dh) * (D ** -0.5)),
            "wo": _w((lambda *s: torch.randn(*s, dtype=torch.bfloat16) * 1.6)(Hq * Dh, D) * ((Hq * Dh) ** -0.5)),
        }
    _A_in = _A_setup()

    def _B_setup():
        B, S, D, F = 1, 1, 576, 4608
        return {
            "x": _w((lambda *s: torch.randn(*s, dtype=torch.bfloat16) * 0.05)(B, S, D)),
            "w_gate": _w((lambda *s: torch.randn(*s, dtype=torch.bfloat16) * 0.05)(D, F)),
            "w_up": _w((lambda *s: torch.randn(*s, dtype=torch.bfloat16) * 0.05)(D, F)),
            "w_down": _w((lambda *s: torch.randn(*s, dtype=torch.bfloat16) * 0.05)(F, D)),
        }
    _B_in = _B_setup()

    return {
        "A_x": _A_in["x"],
        "A_k_cache": _A_in["k_cache"],
        "A_v_cache": _A_in["v_cache"],
        "A_wq": _A_in["wq"],
        "A_wo": _A_in["wo"],
        "B_x": _B_in["x"],
        "B_w_gate": _B_in["w_gate"],
        "B_w_up": _B_in["w_up"],
        "B_w_down": _B_in["w_down"],
    }

def reference(A_x, A_k_cache, A_v_cache, A_wq, A_wo, B_x, B_w_gate, B_w_up, B_w_down):
    def _A_ref(x, k_cache, v_cache, wq, wo):
        B, Sq, D = x.shape
        Hq, Dh = 32, 128
        Hkv, Sk = k_cache.shape[1], k_cache.shape[2]
        W = min(4096, max(256, Sk // 4))
        rep = Hq // Hkv
        q = (lambda x, *d: x.permute(*d))((x @ wq).reshape(B, Sq, Hq, Dh), 0, 2, 1, 3)
        k = (lambda x, n, axis: torch.repeat_interleave(x, n, dim=axis))(k_cache[:, :, Sk - W:, :], rep, axis=1)
        v = (lambda x, n, axis: torch.repeat_interleave(x, n, dim=axis))(v_cache[:, :, Sk - W:, :], rep, axis=1)
        scores = torch.einsum("bhqd,bhkd->bhqk", q, k) * (Dh ** -0.5)
        p = _softmax(scores, axis=-1)
        o = torch.einsum("bhqk,bhkd->bhqd", p, v)
        return (lambda x, *d: x.permute(*d))(o, 0, 2, 1, 3).reshape(B, Sq, Hq * Dh) @ wo

    def _B_ref(x, w_gate, w_up, w_down):
        return (_gelu(x @ w_gate) * (x @ w_up)) @ w_down

    x = A_x
    xn = _layernorm(x, axis=-1)
    return x + _A_ref(xn, A_k_cache, A_v_cache, A_wq, A_wo) + _B_ref(xn, B_w_gate, B_w_up, B_w_down)
```

```cpp
#include <cuda_runtime.h>
#include <cuda_bf16.h>
#include <cuda.h>
#include <stdint.h>

namespace {

constexpr int D_MODEL = 576;
constexpr int SK = 65536;
constexpr int WIN = 4096;
constexpr int NQ = 4096;
constexpr int FF = 4608;
constexpr int NMAIN = 128;
constexpr int NCTA = 132;
constexpr int NRED = 72;
constexpr int NTHREADS = 384;
constexpr int NCOMP = 288;
#define DEPTH 3

constexpr uint32_t KV_BYTES = 16384;
constexpr uint32_t IT_BYTES = 18432;
constexpr uint32_t MISC_OFF = 212992;
constexpr uint32_t OFF_FULL = MISC_OFF;
constexpr uint32_t OFF_EMPTY = MISC_OFF + 256;
constexpr uint32_t OFF_XN = MISC_OFF + 512;
constexpr uint32_t OFF_RED = OFF_XN + 2304;
constexpr uint32_t OFF_Q = OFF_RED + 9216;
constexpr uint32_t OFF_P = OFF_Q + 1024;
constexpr uint32_t OFF_OEX = OFF_P + 4096;
constexpr uint32_t OFF_ML = OFF_OEX + 1152;
constexpr uint32_t SMEM_BYTES = OFF_ML + 128;
static_assert(SMEM_BYTES <= 232448, "smem");

constexpr uint32_t SPIN_LIMIT = 1u << 22;

__device__ __align__(128) uint32_t g_qpart[16][8][256];
__device__ __align__(128) uint32_t g_opart[16][8][8 * 40];
__device__ __align__(128) uint4 g_outpart[NRED][NCTA * 2];

#define STAMP(i)
#define STAMP0(i)

__device__ __forceinline__ uint32_t s2u(const void* p) { return (uint32_t)__cvta_generic_to_shared(p); }
__device__ __forceinline__ void mbar_init(uint32_t a, uint32_t c) { asm volatile("mbarrier.init.shared::cta.b64 [%0], %1;" ::"r"(a), "r"(c) : "memory"); }
__device__ __forceinline__ void mbar_expect(uint32_t a, uint32_t b) { asm volatile("mbarrier.arrive.expect_tx.shared::cta.b64 _, [%0], %1;" ::"r"(a), "r"(b) : "memory"); }
__device__ __forceinline__ void mbar_arrive(uint32_t a) { asm volatile("mbarrier.arrive.shared::cta.b64 _, [%0];" ::"r"(a) : "memory"); }
__device__ __forceinline__ void mbar_wait(uint32_t a) {
    uint32_t ok, n = 0;
    do {
        asm volatile("{\n.reg .pred p;\nmbarrier.try_wait.parity.shared::cta.b64 p, [%1], 0;\nselp.u32 %0, 1, 0, p;\n}" : "=r"(ok) : "r"(a) : "memory");
        if (++n > SPIN_LIMIT) __trap();
    } while (!ok);
}
__device__ __forceinline__ void bulk_ld(uint32_t dst, const void* src, uint32_t bytes, uint32_t bar) {
    asm volatile("cp.async.bulk.shared::cluster.global.mbarrier::complete_tx::bytes [%0], [%1], %2, [%3];" ::"r"(dst), "l"(src), "r"(bytes), "r"(bar) : "memory");
}
__device__ __forceinline__ void tma2d_ld(uint32_t dst, const CUtensorMap* m, int c0, int c1, uint32_t bar) {
    asm volatile("cp.async.bulk.tensor.2d.shared::cluster.global.mbarrier::complete_tx::bytes [%0], [%1, {%3, %4}], [%2];" ::"r"(dst), "l"(m), "r"(bar), "r"(c0), "r"(c1) : "memory");
}
__device__ __forceinline__ uint4 lds128(uint32_t a) { uint4 v; asm volatile("ld.shared.v4.u32 {%0,%1,%2,%3}, [%4];" : "=r"(v.x), "=r"(v.y), "=r"(v.z), "=r"(v.w) : "r"(a)); return v; }
__device__ __forceinline__ float4 lds128f(uint32_t a) { float4 v; asm volatile("ld.shared.v4.f32 {%0,%1,%2,%3}, [%4];" : "=f"(v.x), "=f"(v.y), "=f"(v.z), "=f"(v.w) : "r"(a)); return v; }
__device__ __forceinline__ uint32_t lds32(uint32_t a) { uint32_t v; asm volatile("ld.shared.u32 %0, [%1];" : "=r"(v) : "r"(a)); return v; }
__device__ __forceinline__ float lds32f(uint32_t a) { float v; asm volatile("ld.shared.f32 %0, [%1];" : "=f"(v) : "r"(a)); return v; }
__device__ __forceinline__ void sts32f(uint32_t a, float v) { asm volatile("st.shared.f32 [%0], %1;" ::"r"(a), "f"(v) : "memory"); }
__device__ __forceinline__ void sts128f(uint32_t a, float x, float y, float z, float w) { asm volatile("st.shared.v4.f32 [%0], {%1,%2,%3,%4};" ::"r"(a), "f"(x), "f"(y), "f"(z), "f"(w) : "memory"); }
__device__ __forceinline__ uint4 ldg_nc128(const void* p) { uint4 v; asm volatile("ld.global.nc.L1::no_allocate.v4.u32 {%0,%1,%2,%3}, [%4];" : "=r"(v.x), "=r"(v.y), "=r"(v.z), "=r"(v.w) : "l"(p)); return v; }
__device__ __forceinline__ uint32_t ldg_nc32(const void* p) { uint32_t v; asm volatile("ld.global.nc.u32 %0, [%1];" : "=r"(v) : "l"(p)); return v; }
__device__ __forceinline__ uint32_t ld_rlx(const uint32_t* p) { uint32_t v; asm volatile("ld.relaxed.gpu.global.u32 %0, [%1];" : "=r"(v) : "l"(p) : "memory"); return v; }
__device__ __forceinline__ uint4 ld_rlx128(const uint4* p) { uint4 v; asm volatile("ld.relaxed.gpu.global.v4.u32 {%0,%1,%2,%3}, [%4];" : "=r"(v.x), "=r"(v.y), "=r"(v.z), "=r"(v.w) : "l"(p) : "memory"); return v; }
__device__ __forceinline__ void st_rlx(uint32_t* p, uint32_t v) { asm volatile("st.relaxed.gpu.global.u32 [%0], %1;" ::"l"(p), "r"(v) : "memory"); }
__device__ __forceinline__ void st_rlx64(void* p, uint32_t a, uint32_t b) { asm volatile("st.relaxed.gpu.global.v2.u32 [%0], {%1,%2};" ::"l"(p), "r"(a), "r"(b) : "memory"); }
__device__ __forceinline__ void st_rlx128z(uint4* p) { asm volatile("st.relaxed.gpu.global.v4.u32 [%0], {%1,%1,%1,%1};" ::"l"(p), "r"(0u) : "memory"); }
__device__ __forceinline__ void bar_comp(int id) { asm volatile("bar.sync %0, 288;" ::"r"(id) : "memory"); }

__device__ __forceinline__ float bf_lo(uint32_t u) { return __uint_as_float(u << 16); }
__device__ __forceinline__ float bf_hi(uint32_t u) { return __uint_as_float(u & 0xffff0000u); }
__device__ __forceinline__ float bfr(float v) { return __bfloat162float(__float2bfloat16_rn(v)); }
__device__ __forceinline__ uint32_t enc(float v) { uint32_t u = __float_as_uint(v); return u == 0u ? 0x80000000u : u; }
__device__ __forceinline__ void unpack8(const uint4& u, float (&f)[8]) {
    f[0] = bf_lo(u.x); f[1] = bf_hi(u.x); f[2] = bf_lo(u.y); f[3] = bf_hi(u.y);
    f[4] = bf_lo(u.z); f[5] = bf_hi(u.z); f[6] = bf_lo(u.w); f[7] = bf_hi(u.w);
}

__device__ __forceinline__ void sts32f_p(bool en, uint32_t a, float v) {
    asm volatile("{\n.reg .pred p;\nsetp.ne.u32 p, %2, 0;\n@p st.shared.f32 [%0], %1;\n}" ::"r"(a), "f"(v), "r"((uint32_t)en) : "memory");
}
__device__ __forceinline__ void sts64f_p(bool en, uint32_t a, float x, float y) {
    asm volatile("{\n.reg .pred p;\nsetp.ne.u32 p, %3, 0;\n@p st.shared.v2.f32 [%0], {%1,%2};\n}" ::"r"(a), "f"(x), "f"(y), "r"((uint32_t)en) : "memory");
}
__device__ __forceinline__ void sts128f_p(bool en, uint32_t a, float x, float y, float z, float w) {
    asm volatile("{\n.reg .pred p;\nsetp.ne.u32 p, %5, 0;\n@p st.shared.v4.f32 [%0], {%1,%2,%3,%4};\n}" ::"r"(a), "f"(x), "f"(y), "f"(z), "f"(w), "r"((uint32_t)en) : "memory");
}
__device__ __forceinline__ void st_rlx_p(bool en, uint32_t* p, uint32_t v) {
    asm volatile("{\n.reg .pred p;\nsetp.ne.u32 p, %2, 0;\n@p st.relaxed.gpu.global.u32 [%0], %1;\n}" ::"l"(p), "r"(v), "r"((uint32_t)en) : "memory");
}
__device__ __forceinline__ void st_rlx64_p(bool en, void* p, uint32_t a, uint32_t b) {
    asm volatile("{\n.reg .pred p;\nsetp.ne.u32 p, %3, 0;\n@p st.relaxed.gpu.global.v2.u32 [%0], {%1,%2};\n}" ::"l"(p), "r"(a), "r"(b), "r"((uint32_t)en) : "memory");
}
__device__ __forceinline__ void mbar_arrive_p(bool en, uint32_t a) {
    asm volatile("{\n.reg .pred p;\nsetp.ne.u32 p, %1, 0;\n@p mbarrier.arrive.shared::cta.b64 _, [%0];\n}" ::"r"(a), "r"((uint32_t)en) : "memory");
}
__device__ __forceinline__ void bar_comp_p(bool en, int id) {
    asm volatile("{\n.reg .pred p;\nsetp.ne.u32 p, %1, 0;\n@p bar.sync %0, 288;\n}" ::"r"(id), "r"((uint32_t)en) : "memory");
}
__device__ __forceinline__ void mbar_wait_p(bool en, uint32_t a) {
    uint32_t ok, n = 0;
    do {
        asm volatile("{\n.reg .pred p;\nmbarrier.try_wait.parity.shared::cta.b64 p, [%1], %2;\nselp.u32 %0, 1, 0, p;\n}" : "=r"(ok) : "r"(a), "r"((uint32_t)!en) : "memory");
        if (++n > SPIN_LIMIT) __trap();
    } while (!ok && en);
}

__global__ void __launch_bounds__(NTHREADS, 1)
fused_decode_kernel(const __nv_bfloat16* __restrict__ x, const uint8_t* __restrict__ kc, const uint8_t* __restrict__ vc,
                    const uint8_t* __restrict__ wq, const uint8_t* __restrict__ wo, const uint8_t* __restrict__ wd,
                    __nv_bfloat16* __restrict__ out,
                    const __grid_constant__ CUtensorMap tg, const __grid_constant__ CUtensorMap tu) {
    extern __shared__ __align__(1024) uint8_t smem[];
    const uint32_t sb = s2u(smem);
    const int lane = threadIdx.x & 31, wid = threadIdx.x >> 5;
    const int b = blockIdx.x, h = b >> 3, s = b & 7;
    const bool is_main = b < NMAIN;
    const uint32_t full = sb + OFF_FULL, empty = sb + OFF_EMPTY;
    const uint32_t bar_q = sb + OFF_FULL + 24 * 8, bar_o = bar_q + 8;

    const size_t kvoff = ((size_t)h * SK + (SK - WIN) + s * 512) * 256;
    if (threadIdx.x == 9 * 32 && is_main) {
        mbar_init(full, 1);
        mbar_init(full + 8, 1);
        mbar_expect(full, KV_BYTES);
        bulk_ld(sb, kc + kvoff, KV_BYTES, full);
        mbar_expect(full + 8, KV_BYTES);
        bulk_ld(sb + KV_BYTES, kc + kvoff + KV_BYTES, KV_BYTES, full + 8);
    }
    uint4 wreg[8];
    {
        const uint8_t* p = wq + (size_t)(s * 72 + wid * 8) * (NQ * 2) + h * 512 + lane * 16;
        const uint32_t ld = is_main && wid < 9;
#pragma unroll
        for (int r = 0; r < 8; r++)
            asm volatile("{\n.reg .pred p;\nsetp.ne.u32 p, %5, 0;\n@p ld.global.nc.L1::no_allocate.v4.u32 {%0,%1,%2,%3}, [%4];\n}"
                         : "=r"(wreg[r].x), "=r"(wreg[r].y), "=r"(wreg[r].z), "=r"(wreg[r].w) : "l"(p + (size_t)r * (NQ * 2)), "r"(ld));
    }

    if (wid == 9) {
        if (lane == 0) {
            if (!is_main) { mbar_init(full, 1); mbar_init(full + 8, 1); }
#pragma unroll
            for (int i = 2; i < 24; i++) mbar_init(full + i * 8, 1);
            mbar_init(bar_q, 32);
            mbar_init(bar_o, 32);
            const uint32_t cnt = is_main ? 8 : 9;
#pragma unroll
            for (int i = 0; i < 13; i++) mbar_init(empty + i * 8, cnt);
        }
        __syncwarp();
        asm volatile("bar.arrive 15, 384;" ::: "memory");
        {
            const int i = lane;
            const int j = is_main ? i - 16 : i % 6;
            const int unit = is_main ? b : NMAIN + (b - NMAIN) * 4 + i / 6;
            const uint32_t off = is_main ? (i < 12 ? i * KV_BYTES : i < 16 ? (i - 12) * KV_BYTES : 65536u + (i - 16) * IT_BYTES) : (i % 11) * IT_BYTES;
            const int dep = is_main ? (i < 16 ? i - 12 : min(i - 11, 11)) : i - 11;
            const int prev = is_main ? max(i - DEPTH, 0) : i - DEPTH;
            const uint32_t bytes = j < 0 ? KV_BYTES : IT_BYTES;
            const uint8_t* src = j < 0 ? (i < 8 ? kc : vc) + kvoff + (i & 7) * KV_BYTES
                                       : (j < 6 ? wd : wo) + (size_t)unit * 36864 + (j & 1) * IT_BYTES;
            const uint32_t dst = sb + off, bar = full + i * 8;
            const int i0 = is_main ? 2 : 0;
            if (i >= i0 && i < 24) mbar_expect(bar, bytes);
            if (lane == 31) {
                asm volatile("prefetch.tensormap [%0];" ::"l"(&tg) : "memory");
                asm volatile("prefetch.tensormap [%0];" ::"l"(&tu) : "memory");
            }
#pragma unroll 1
            for (int k = i0; k < 24; k++) {
                if (lane == k) {
                    if (prev >= 0) mbar_wait(full + prev * 8);
                    if (dep >= 0) mbar_wait(empty + dep * 8);
                    if (j >= 0 && j < 4) {
                        tma2d_ld(dst, &tg, unit * 32, j * 144, bar);
                        tma2d_ld(dst + 9216, &tu, unit * 32, j * 144, bar);
                    } else {
                        bulk_ld(dst, src, bytes, bar);
                    }
                }
                __syncwarp();
            }
        }
        if (b < NRED) {
            const uint2 xr = *reinterpret_cast<const uint2*>(x + b * 8 + (lane & 1) * 4);
            uint4* slot = &g_outpart[b][lane];
            uint4 v[9];
            uint32_t pend = lane < 8 ? 0x1ffu : 0xffu;
            v[8] = make_uint4(0x80000000u, 0x80000000u, 0x80000000u, 0x80000000u);
#pragma unroll 1
            for (uint32_t n = 0;; n++) {
#pragma unroll
                for (int i = 0; i < 9; i++)
                    if (pend >> i & 1) v[i] = ld_rlx128(slot + i * 32);
                float a0 = 0.f, a1 = 0.f, a2 = 0.f, a3 = 0.f;
#pragma unroll
                for (int i = 0; i < 9; i++) {
                    if (v[i].x && v[i].y && v[i].z && v[i].w) pend &= ~(1u << i);
                    a0 += __uint_as_float(v[i].x); a1 += __uint_as_float(v[i].y);
                    a2 += __uint_as_float(v[i].z); a3 += __uint_as_float(v[i].w);
                }
                const bool done = __all_sync(0xffffffffu, pend == 0u);
                const bool b2 = lane & 2;
                float k0 = (b2 ? a2 : a0) + __shfl_xor_sync(0xffffffffu, b2 ? a0 : a2, 2);
                float k1 = (b2 ? a3 : a1) + __shfl_xor_sync(0xffffffffu, b2 ? a1 : a3, 2);
#pragma unroll
                for (int o = 4; o < 32; o <<= 1) {
                    k0 += __shfl_xor_sync(0xffffffffu, k0, o);
                    k1 += __shfl_xor_sync(0xffffffffu, k1, o);
                }
                const uint32_t xw = b2 ? xr.y : xr.x;
                __nv_bfloat162 r = __floats2bfloat162_rn(k0 + bf_lo(xw), k1 + bf_hi(xw));
                if (done) {
                    if (lane < 4) *reinterpret_cast<__nv_bfloat162*>(out + b * 8 + (lane & 1) * 4 + (lane & 2)) = r;
                    break;
                }
                if (n == 0) mbar_wait(full + 23 * 8);
                if (n > SPIN_LIMIT) __trap();
            }
#pragma unroll
            for (int i = 0; i < 9; i++)
                if (i < 8 || lane < 8) st_rlx128z(slot + i * 32);
        }
        return;
    }
    if (wid == 10) {
        asm volatile("bar.arrive 15, 384;" ::: "memory");
        if (!is_main) return;
        {
            const uint4* src = reinterpret_cast<const uint4*>(&g_qpart[h][0][0]);
            uint32_t n = 0;
            for (;;) {
                const uint32_t f = ld_rlx(&g_qpart[h][lane & 7][255]);
                if (__all_sync(0xffffffffu, f != 0u)) break;
                if (++n > SPIN_LIMIT) __trap();
                __nanosleep(100);
            }
            float q[8];
            for (;;) {
                bool ok = true;
#pragma unroll
                for (int i = 0; i < 8; i++) q[i] = 0.f;
#pragma unroll
                for (int i = 0; i < 8; i++) {
                    const uint4 a = ld_rlx128(src + i * 64 + lane), c = ld_rlx128(src + i * 64 + 32 + lane);
                    ok = ok && a.x && a.y && a.z && a.w && c.x && c.y && c.z && c.w;
                    q[0] += __uint_as_float(a.x); q[1] += __uint_as_float(a.y); q[2] += __uint_as_float(a.z); q[3] += __uint_as_float(a.w);
                    q[4] += __uint_as_float(c.x); q[5] += __uint_as_float(c.y); q[6] += __uint_as_float(c.z); q[7] += __uint_as_float(c.w);
                }
                if (ok) break;
                if (++n > SPIN_LIMIT) __trap();
            }
            sts128f(sb + OFF_Q + lane * 16, bfr(q[0]), bfr(q[1]), bfr(q[2]), bfr(q[3]));
            sts128f(sb + OFF_Q + 512 + lane * 16, bfr(q[4]), bfr(q[5]), bfr(q[6]), bfr(q[7]));
            mbar_arrive(bar_q);
        }
        {
            uint32_t* slot = &g_opart[h][s][0];
            uint32_t n = 0, ml;
            for (;;) {
                ml = ld_rlx(slot + (lane >> 2) * 40 + 32 + (lane & 3));
                if (__all_sync(0xffffffffu, ml != 0u)) break;
                if (++n > SPIN_LIMIT) __trap();
                __nanosleep(200);
            }
            uint32_t ov[8];
            for (;;) {
                bool ok = true;
#pragma unroll
                for (int i = 0; i < 8; i++) { ov[i] = ld_rlx(slot + i * 40 + lane); ok = ok && ov[i]; }
                if (ok) break;
                if (++n > SPIN_LIMIT) __trap();
            }
            __syncwarp();
            const float mlf = __uint_as_float(ml);
            float M = mlf;
            M = fmaxf(M, __shfl_xor_sync(0xffffffffu, M, 4));
            M = fmaxf(M, __shfl_xor_sync(0xffffffffu, M, 8));
            M = fmaxf(M, __shfl_xor_sync(0xffffffffu, M, 16));
            const float e = __expf(mlf - M);
            float o = 0.f, L = 0.f;
#pragma unroll
            for (int i = 0; i < 8; i++) {
                const float ei = __shfl_sync(0xffffffffu, e, i * 4);
                o = fmaf(ei, __uint_as_float(ov[i]), o);
                L = fmaf(ei, __shfl_sync(0xffffffffu, mlf, i * 4 + 1), L);
            }
            sts32f(sb + OFF_OEX + lane * 4, bfr(o / L));
            mbar_arrive(bar_o);
            uint4* z = reinterpret_cast<uint4*>(slot);
            st_rlx128z(z + lane); st_rlx128z(z + 32 + lane);
            if (lane < 16) st_rlx128z(z + 64 + lane);
            z = reinterpret_cast<uint4*>(&g_qpart[h][s][0]);
            st_rlx128z(z + lane); st_rlx128z(z + 32 + lane);
        }
        return;
    }

    const bool en = wid < 9;
    const int w = en ? wid : 0, t = w * 32 + lane;
    float acc0 = 0.f, acc1 = 0.f;
    if (en) {
        STAMP0(0);
        const uint32_t* x32 = reinterpret_cast<const uint32_t*>(x);
        uint32_t xa[9];
#pragma unroll
        for (int i = 0; i < 9; i++) xa[i] = ldg_nc32(x32 + i * 32 + lane);
        const uint32_t mine = ldg_nc32(x32 + t);
        const uint32_t xrow = ldg_nc32(x32 + s * 36 + w * 4 + (lane & 3));
        float sum = 0.f;
#pragma unroll
        for (int i = 0; i < 9; i++) sum += bf_lo(xa[i]) + bf_hi(xa[i]);
#pragma unroll
        for (int o = 16; o; o >>= 1) sum += __shfl_xor_sync(0xffffffffu, sum, o);
        const float mean = sum * (1.0f / D_MODEL);
        float sq = 0.f;
#pragma unroll
        for (int i = 0; i < 9; i++) { float a = bf_lo(xa[i]) - mean, c = bf_hi(xa[i]) - mean; sq += a * a + c * c; }
#pragma unroll
        for (int o = 16; o; o >>= 1) sq += __shfl_xor_sync(0xffffffffu, sq, o);
        const float m_bf = bfr(mean);
        const float sd = bfr(sqrtf(bfr(bfr(sq * (1.0f / D_MODEL)) + 1e-5f)));
        sts64f_p(true, sb + OFF_XN + t * 8, bfr(__fdividef(bfr(bf_lo(mine) - m_bf), sd)), bfr(__fdividef(bfr(bf_hi(mine) - m_bf), sd)));
        if (is_main) {
            const float xlo = bfr(__fdividef(bfr(bf_lo(xrow) - m_bf), sd)), xhi = bfr(__fdividef(bfr(bf_hi(xrow) - m_bf), sd));
            float qa[8];
#pragma unroll
            for (int i = 0; i < 8; i++) qa[i] = 0.f;
#pragma unroll
            for (int r = 0; r < 8; r++) {
                const float xv = __shfl_sync(0xffffffffu, (r & 1) ? xhi : xlo, r >> 1);
                float f[8];
                unpack8(wreg[r], f);
#pragma unroll
                for (int i = 0; i < 8; i++) qa[i] = fmaf(xv, f[i], qa[i]);
            }
            const uint32_t dst = sb + OFF_RED + w * 1024 + lane * 32;
            sts128f(dst, qa[0], qa[1], qa[2], qa[3]);
            sts128f(dst + 16, qa[4], qa[5], qa[6], qa[7]);
        }
        STAMP0(1);
        asm volatile("bar.sync 15, 384;" ::: "memory");
        if (is_main && t < 256) {
            float v = 0.f;
#pragma unroll
            for (int i = 0; i < 9; i++) v += lds32f(sb + OFF_RED + i * 1024 + t * 4);
            st_rlx(&g_qpart[h][s][t], enc(v));
        }
        STAMP0(2);
    } else {
        asm volatile("bar.arrive 15, 384;" ::: "memory");
    }
    const int nch = en ? 8 : 1;

    if (is_main) {
        if (w < 8) {
            const int hf = lane >> 4, l16 = lane & 15;
            if (en) mbar_wait(bar_q);
            STAMP0(3);
            float qa[8], qb[8];
            {
                float4 a = lds128f(sb + OFF_Q + l16 * 32), c = lds128f(sb + OFF_Q + l16 * 32 + 16);
                qa[0] = a.x; qa[1] = a.y; qa[2] = a.z; qa[3] = a.w; qa[4] = c.x; qa[5] = c.y; qa[6] = c.z; qa[7] = c.w;
                a = lds128f(sb + OFF_Q + 512 + l16 * 32); c = lds128f(sb + OFF_Q + 512 + l16 * 32 + 16);
                qb[0] = a.x; qb[1] = a.y; qb[2] = a.z; qb[3] = a.w; qb[4] = c.x; qb[5] = c.y; qb[6] = c.z; qb[7] = c.w;
            }
            const uint32_t loff = sb + (w * 8 + hf) * 256 + l16 * 16;
            const bool b8 = lane & 8, b4 = lane & 4, b2 = lane & 2;
            const uint32_t pw = sb + OFF_P + w * 512;
            float m = -INFINITY;
#pragma unroll 1
            for (int c = 0; c < nch; c++) {
                if (en) mbar_wait(full + c * 8);
                uint4 kv[4];
#pragma unroll
                for (int j = 0; j < 4; j++) kv[j] = lds128(loff + c * KV_BYTES + j * 512);
                float v[8];
#pragma unroll
                for (int j = 0; j < 4; j++) {
                    float f[8];
                    unpack8(kv[j], f);
                    float a = f[0] * qa[0], e = f[0] * qb[0];
#pragma unroll
                    for (int i = 1; i < 8; i++) { a = fmaf(f[i], qa[i], a); e = fmaf(f[i], qb[i], e); }
                    v[2 * j] = a; v[2 * j + 1] = e;
                }
                __syncwarp();
                mbar_arrive_p(en && lane == 0, empty + c * 8);
                float k4[4], k2[2];
#pragma unroll
                for (int i = 0; i < 4; i++) k4[i] = (b8 ? v[i + 4] : v[i]) + __shfl_xor_sync(0xffffffffu, b8 ? v[i] : v[i + 4], 8);
#pragma unroll
                for (int i = 0; i < 2; i++) k2[i] = (b4 ? k4[i + 2] : k4[i]) + __shfl_xor_sync(0xffffffffu, b4 ? k4[i] : k4[i + 2], 4);
                float k1 = (b2 ? k2[1] : k2[0]) + __shfl_xor_sync(0xffffffffu, b2 ? k2[0] : k2[1], 2);
                k1 += __shfl_xor_sync(0xffffffffu, k1, 1);
                const float sc = bfr(bfr(k1) * 0.08838834764831845f);
                m = fmaxf(m, sc);
                sts32f_p(en, pw + c * 64 + (lane >> 1) * 4, sc);
            }
            STAMP0(4);
            m = fmaxf(m, __shfl_xor_sync(0xffffffffu, m, 4));
            m = fmaxf(m, __shfl_xor_sync(0xffffffffu, m, 8));
            m = fmaxf(m, __shfl_xor_sync(0xffffffffu, m, 16));
            const float m0 = __shfl_sync(0xffffffffu, m, 0), m1 = __shfl_sync(0xffffffffu, m, 2);
            __syncwarp();
            {
                const float4 sv = lds128f(pw + lane * 16);
                const float p0 = __expf(sv.x - m0), p1 = __expf(sv.y - m1), p2 = __expf(sv.z - m0), p3 = __expf(sv.w - m1);
                sts128f_p(en, pw + lane * 16, p0, p1, p2, p3);
                float l = (b2 ? p1 + p3 : p0 + p2) + __shfl_xor_sync(0xffffffffu, b2 ? p0 + p2 : p1 + p3, 2);
                l += __shfl_xor_sync(0xffffffffu, l, 1);
                l += __shfl_xor_sync(0xffffffffu, l, 4);
                l += __shfl_xor_sync(0xffffffffu, l, 8);
                l += __shfl_xor_sync(0xffffffffu, l, 16);
                sts64f_p(en && (lane & 29) == 0, sb + OFF_ML + (lane >> 1) * 64 + w * 8, m, l);
            }
            __syncwarp();
            float oa[8], ob[8];
#pragma unroll
            for (int i = 0; i < 8; i++) { oa[i] = 0.f; ob[i] = 0.f; }
#pragma unroll 1
            for (int c = 0; c < nch; c++) {
                const float4 p01 = lds128f(pw + c * 64 + hf * 32), p23 = lds128f(pw + c * 64 + hf * 32 + 16);
                const float pa[4] = {p01.x, p01.z, p23.x, p23.z}, pb[4] = {p01.y, p01.w, p23.y, p23.w};
                if (en) mbar_wait(full + (8 + c) * 8);
                const uint32_t vb = loff + (c < 4 ? c + 8 : c - 4) * KV_BYTES;
                uint4 vv[4];
#pragma unroll
                for (int j = 0; j < 4; j++) vv[j] = lds128(vb + j * 512);
#pragma unroll
                for (int j = 0; j < 4; j++) {
                    float f[8];
                    unpack8(vv[j], f);
#pragma unroll
                    for (int i = 0; i < 8; i++) { oa[i] = fmaf(pa[j], f[i], oa[i]); ob[i] = fmaf(pb[j], f[i], ob[i]); }
                }
                __syncwarp();
                mbar_arrive_p(en && lane == 0 && c < 4, empty + (8 + c) * 8);
            }
            float o8[8];
#pragma unroll
            for (int i = 0; i < 8; i++) o8[i] = (hf ? ob[i] : oa[i]) + __shfl_xor_sync(0xffffffffu, hf ? oa[i] : ob[i], 16);
            const uint32_t dst = sb + OFF_RED + w * 1024 + lane * 32;
            sts128f_p(en, dst, o8[0], o8[1], o8[2], o8[3]);
            sts128f_p(en, dst + 16, o8[4], o8[5], o8[6], o8[7]);
        }
        STAMP0(5);
        bar_comp_p(en, 2);
        if (w < 8) {
            const uint32_t ml = sb + OFF_ML + (t >> 7) * 64;
            float mm[8], ll[8];
#pragma unroll
            for (int i = 0; i < 4; i++) { float4 a = lds128f(ml + i * 16); mm[2 * i] = a.x; ll[2 * i] = a.y; mm[2 * i + 1] = a.z; ll[2 * i + 1] = a.w; }
            float M = mm[0];
#pragma unroll
            for (int i = 1; i < 8; i++) M = fmaxf(M, mm[i]);
            float o = 0.f, L = 0.f;
#pragma unroll
            for (int i = 0; i < 8; i++) {
                float e = __expf(mm[i] - M);
                o = fmaf(e, lds32f(sb + OFF_RED + i * 1024 + t * 4), o);
                L = fmaf(e, ll[i], L);
            }
            uint32_t* dst = &g_opart[h][w][s * 40];
            st_rlx_p(en, dst + lane, enc(o));
            st_rlx_p(en && lane < 8, dst + 32 + lane, enc((lane & 1) ? L : M));
        }
        STAMP0(6);
    }

    {
        int it = is_main ? 16 : 0;
        uint32_t off = is_main ? 65536u : 0u;
        const int nunits = (is_main || !en) ? 1 : 4;
        const int ngu = en ? 4 : 1, nrow = en ? (is_main ? 4 : 2) : 1;
        const bool b16 = lane & 16, b8 = lane & 8, b4 = lane & 4;
#pragma unroll 1
        for (int u = 0; u < nunits; u++) {
            float ag[8], au[8];
#pragma unroll
            for (int i = 0; i < 8; i++) { ag[i] = 0.f; au[i] = 0.f; }
#pragma unroll 1
            for (int j = 0; j < ngu; j++) {
                const uint32_t xa = sb + OFF_XN + (j * 144 + (t >> 2)) * 4;
                const float x0 = lds32f(xa), x1 = lds32f(xa + 72 * 4);
                if (en) mbar_wait(full + it * 8);
                const uint32_t base = sb + off + t * 16;
                const uint4 g0 = lds128(base), g1 = lds128(base + 4608), u0 = lds128(base + 9216), u1 = lds128(base + 13824);
                float f[8];
                unpack8(g0, f);
#pragma unroll
                for (int i = 0; i < 8; i++) ag[i] = fmaf(x0, f[i], ag[i]);
                unpack8(g1, f);
#pragma unroll
                for (int i = 0; i < 8; i++) ag[i] = fmaf(x1, f[i], ag[i]);
                unpack8(u0, f);
#pragma unroll
                for (int i = 0; i < 8; i++) au[i] = fmaf(x0, f[i], au[i]);
                unpack8(u1, f);
#pragma unroll
                for (int i = 0; i < 8; i++) au[i] = fmaf(x1, f[i], au[i]);
                __syncwarp();
                mbar_arrive_p(en && lane == 0 && it < 13, empty + it * 8);
                it++; off += IT_BYTES;
                if (off == 11 * IT_BYTES) off = 0;
            }
            STAMP0(7);
            const uint32_t red = is_main ? sb + OFF_P : sb + OFF_RED + (u & 1) * 2304;
            {
                float k8[8], k4[4], k2[2];
#pragma unroll
                for (int i = 0; i < 8; i++) k8[i] = (b16 ? au[i] : ag[i]) + __shfl_xor_sync(0xffffffffu, b16 ? ag[i] : au[i], 16);
#pragma unroll
                for (int i = 0; i < 4; i++) k4[i] = (b8 ? k8[i + 4] : k8[i]) + __shfl_xor_sync(0xffffffffu, b8 ? k8[i] : k8[i + 4], 8);
#pragma unroll
                for (int i = 0; i < 2; i++) k2[i] = (b4 ? k4[i + 2] : k4[i]) + __shfl_xor_sync(0xffffffffu, b4 ? k4[i] : k4[i + 2], 4);
                const int idx = (b16 ? 32 : 0) + (lane & 3) * 8 + (b8 ? 4 : 0) + (b4 ? 2 : 0);
                sts64f_p(en, red + w * 256 + idx * 4, k2[0], k2[1]);
            }
            bar_comp_p(en, 3);
            float coef;
            {
                float g = 0.f, uu = 0.f;
#pragma unroll
                for (int k = 0; k < 9; k++) { g += lds32f(red + k * 256 + lane * 4); uu += lds32f(red + k * 256 + 128 + lane * 4); }
                g = bfr(g); uu = bfr(uu);
                const float inner = 0.7978845608028654f * (g + 0.044715f * g * g * g);
                const float ge = bfr(__fdividef(g, 1.0f + __expf(-2.0f * inner)));
                coef = bfr(ge * uu);
            }
#pragma unroll 1
            for (int j = 0; j < nrow; j++) {
                if (j == 2) {
                    STAMP0(9);
                    mbar_wait(bar_o);
                    coef = lds32f(sb + OFF_OEX + lane * 4);
                }
                if (en) mbar_wait(full + it * 8);
                const uint32_t base = sb + off + t * 4;
                const int r0 = (j & 1) * 16;
#pragma unroll
                for (int r = 0; r < 16; r++) {
                    const uint32_t wv = lds32(base + r * 1152);
                    const float c = __shfl_sync(0xffffffffu, coef, r0 + r);
                    acc0 = fmaf(c, bf_lo(wv), acc0);
                    acc1 = fmaf(c, bf_hi(wv), acc1);
                }
                __syncwarp();
                mbar_arrive_p(en && lane == 0 && it < 13, empty + it * 8);
                it++; off += IT_BYTES;
                if (off == 11 * IT_BYTES) off = 0;
            }
        }
    }
    st_rlx64_p(en, reinterpret_cast<uint32_t*>(&g_outpart[t >> 2][b * 2]) + (t & 3) * 2, enc(acc0), enc(acc1));
    STAMP0(11);
}

typedef CUresult (*EncodeFn)(CUtensorMap*, CUtensorMapDataType, cuuint32_t, void*, const cuuint64_t*, const cuuint64_t*,
                             const cuuint32_t*, const cuuint32_t*, CUtensorMapInterleave, CUtensorMapSwizzle,
                             CUtensorMapL2promotion, CUtensorMapFloatOOBfill);

void make_map(EncodeFn fn, CUtensorMap* m, const void* p) {
    cuuint64_t gd[2] = {(cuuint64_t)FF, (cuuint64_t)D_MODEL};
    cuuint64_t gs[1] = {(cuuint64_t)FF * 2};
    cuuint32_t bd[2] = {32, 144};
    cuuint32_t es[2] = {1, 1};
    fn(m, CU_TENSOR_MAP_DATA_TYPE_BFLOAT16, 2, const_cast<void*>(p), gd, gs, bd, es, CU_TENSOR_MAP_INTERLEAVE_NONE,
       CU_TENSOR_MAP_SWIZZLE_NONE, CU_TENSOR_MAP_L2_PROMOTION_L2_128B, CU_TENSOR_MAP_FLOAT_OOB_FILL_NONE);
}

}

extern "C" void kernel_launch(void* const* d_in, const int* in_sizes, int n_in, void* d_out, int out_size) {
    (void)in_sizes; (void)n_in; (void)out_size;
    static EncodeFn enc_fn = nullptr;
    if (!enc_fn) {
        cudaDriverEntryPointQueryResult qr;
        void* fn = nullptr;
        cudaGetDriverEntryPoint("cuTensorMapEncodeTiled", &fn, cudaEnableDefault, &qr);
        enc_fn = (EncodeFn)fn;
        cudaFuncSetAttribute(fused_decode_kernel, cudaFuncAttributeMaxDynamicSharedMemorySize, SMEM_BYTES);
    }
    CUtensorMap tg, tu;
    make_map(enc_fn, &tg, d_in[6]);
    make_map(enc_fn, &tu, d_in[7]);
    fused_decode_kernel<<<NCTA, NTHREADS, SMEM_BYTES>>>(
        (const __nv_bfloat16*)d_in[0], (const uint8_t*)d_in[1], (const uint8_t*)d_in[2], (const uint8_t*)d_in[3],
        (const uint8_t*)d_in[4], (const uint8_t*)d_in[8], (__nv_bfloat16*)d_out, tg, tu);
}
```

```cpp
#include <cuda_runtime.h>
#include <cuda_bf16.h>
#include <cuda.h>
#include <stdint.h>

namespace {

constexpr int D_MODEL = 576;
constexpr int SK = 65536;
constexpr int WIN = 4096;
constexpr int NQ = 4096;
constexpr int FF = 4608;
constexpr int NMAIN = 128;
constexpr int NCTA = 132;
constexpr int NRED = 72;
constexpr int NTHREADS = 352;
#define ROT 0
#define INIT4 1
#define LATE_FROM 99
#define LATE_DEPTH 6
#define PACE 1
#define PACE_W0 20000
#define PACE_PS_PER_B 41
#define PACE_STAGGER 1
#define OPOLL_FROM 17
#define OPOLL_SLEEP 100
#define QPOLL_FROM 3
#define FPOLL_AT 0
#define KVIL 1
#define PROMO 2
#define KVROT 0
#define QEARLY 0
#define OEARLY 0
#define DEPTH 6

constexpr uint32_t KV_BYTES = 16384;
constexpr uint32_t IT_BYTES = 18432;
constexpr uint32_t WQ_OFF = 176128;
constexpr uint32_t MISC_OFF = 212992;
constexpr uint32_t OFF_FULL = MISC_OFF;
constexpr uint32_t OFF_EMPTY = MISC_OFF + 256;
constexpr uint32_t OFF_XN = MISC_OFF + 512;
constexpr uint32_t OFF_RED = OFF_XN + 1152;
constexpr uint32_t OFF_Q = OFF_RED + 9216;
constexpr uint32_t OFF_S = OFF_Q + 512;
constexpr uint32_t OFF_P = OFF_S + 4096;
constexpr uint32_t OFF_OEX = OFF_P + 2048;
constexpr uint32_t OFF_ML = OFF_OEX + 128;
constexpr uint32_t OFF_EP = OFF_ML + 128;
constexpr uint32_t OFF_FIN = OFF_EP + 16;
constexpr uint32_t SMEM_BYTES = OFF_FIN + 384;
static_assert(SMEM_BYTES <= 232448, "smem");

constexpr uint32_t SPIN_LIMIT = 1u << 22;

struct Scratch {
    uint4 q[16][64];
    uint32_t opart[16][8][8 * 32];
    uint4 outpart[NRED][NCTA * 2];
    uint32_t epoch;
};
__device__ __align__(128) Scratch g_scratch;
#define g_q sc_->q
#define g_opart sc_->opart
#define g_outpart sc_->outpart
#define g_tl sc_->tl

struct Maps { CUtensorMap m[5]; };

__device__ __forceinline__ uint32_t gtime32() { uint32_t t; asm volatile("mov.u32 %0, %globaltimer_lo;" : "=r"(t)); return t; }
#define STAMP(i)
#define STAMP0(i)

__device__ __forceinline__ uint32_t s2u(const void* p) { return (uint32_t)__cvta_generic_to_shared(p); }
__device__ __forceinline__ void mbar_init(uint32_t a, uint32_t c) { asm volatile("mbarrier.init.shared::cta.b64 [%0], %1;" ::"r"(a), "r"(c) : "memory"); }
__device__ __forceinline__ void mbar_expect(uint32_t a, uint32_t b) { asm volatile("mbarrier.arrive.expect_tx.shared::cta.b64 _, [%0], %1;" ::"r"(a), "r"(b) : "memory"); }
__device__ __forceinline__ void mbar_wait(uint32_t a) {
    uint32_t ok, n = 0;
    do {
        asm volatile("{\n.reg .pred p;\nmbarrier.try_wait.parity.shared::cta.b64 p, [%1], 0;\nselp.u32 %0, 1, 0, p;\n}" : "=r"(ok) : "r"(a) : "memory");
        if (++n > SPIN_LIMIT) __trap();
    } while (!ok);
}
__device__ __forceinline__ void bulk_ld(uint32_t dst, const void* src, uint32_t bytes, uint32_t bar) {
    asm volatile("cp.async.bulk.shared::cluster.global.mbarrier::complete_tx::bytes [%0], [%1], %2, [%3];" ::"r"(dst), "l"(src), "r"(bytes), "r"(bar) : "memory");
}
__device__ __forceinline__ void tma2d_ld(uint32_t dst, const CUtensorMap* m, int c0, int c1, uint32_t bar) {
    asm volatile("cp.async.bulk.tensor.2d.shared::cluster.global.mbarrier::complete_tx::bytes [%0], [%1, {%3, %4}], [%2];" ::"r"(dst), "l"(m), "r"(bar), "r"(c0), "r"(c1) : "memory");
}
__device__ __forceinline__ uint4 lds128(uint32_t a) { uint4 v; asm volatile("ld.shared.v4.u32 {%0,%1,%2,%3}, [%4];" : "=r"(v.x), "=r"(v.y), "=r"(v.z), "=r"(v.w) : "r"(a) : "memory"); return v; }
__device__ __forceinline__ float4 lds128f(uint32_t a) { float4 v; asm volatile("ld.shared.v4.f32 {%0,%1,%2,%3}, [%4];" : "=f"(v.x), "=f"(v.y), "=f"(v.z), "=f"(v.w) : "r"(a) : "memory"); return v; }
__device__ __forceinline__ uint32_t lds32(uint32_t a) { uint32_t v; asm volatile("ld.shared.u32 %0, [%1];" : "=r"(v) : "r"(a) : "memory"); return v; }
__device__ __forceinline__ float lds32f(uint32_t a) { float v; asm volatile("ld.shared.f32 %0, [%1];" : "=f"(v) : "r"(a) : "memory"); return v; }
__device__ __forceinline__ uint4 ldsm4t(uint32_t a) {
    uint4 v;
    asm volatile("ldmatrix.sync.aligned.m8n8.x4.trans.shared.b16 {%0,%1,%2,%3}, [%4];" : "=r"(v.x), "=r"(v.y), "=r"(v.z), "=r"(v.w) : "r"(a) : "memory");
    return v;
}
__device__ __forceinline__ void mma16(float (&c)[4], uint32_t a0, uint32_t a1, uint32_t a2, uint32_t a3, uint32_t b0, uint32_t b1) {
    asm volatile("mma.sync.aligned.m16n8k16.row.col.f32.bf16.bf16.f32 {%0,%1,%2,%3}, {%4,%5,%6,%7}, {%8,%9}, {%0,%1,%2,%3};"
                 : "+f"(c[0]), "+f"(c[1]), "+f"(c[2]), "+f"(c[3]) : "r"(a0), "r"(a1), "r"(a2), "r"(a3), "r"(b0), "r"(b1));
}
__device__ __forceinline__ void mma8(float (&c)[4], uint32_t a0, uint32_t a1, uint32_t b0) {
    asm volatile("mma.sync.aligned.m16n8k8.row.col.f32.bf16.bf16.f32 {%0,%1,%2,%3}, {%4,%5}, {%6}, {%0,%1,%2,%3};"
                 : "+f"(c[0]), "+f"(c[1]), "+f"(c[2]), "+f"(c[3]) : "r"(a0), "r"(a1), "r"(b0));
}
__device__ __forceinline__ uint32_t ldg_nc32(const void* p) { uint32_t v; asm volatile("ld.global.nc.u32 %0, [%1];" : "=r"(v) : "l"(p)); return v; }
template <int R> __device__ __forceinline__ uint4 ldg_row(const uint8_t* p, bool en) {
    uint4 v;
    asm volatile("{\n.reg .pred p;\nsetp.ne.u32 p, %5, 0;\n@p ld.global.nc.L1::no_allocate.v4.u32 {%0,%1,%2,%3}, [%4 + %6];\n}"
                 : "=r"(v.x), "=r"(v.y), "=r"(v.z), "=r"(v.w) : "l"(p), "r"((uint32_t)en), "n"(R * NQ * 2));
    return v;
}
__device__ __forceinline__ uint32_t ld_rlx(const uint32_t* p) { uint32_t v; asm volatile("ld.relaxed.gpu.global.u32 %0, [%1];" : "=r"(v) : "l"(p) : "memory"); return v; }
__device__ __forceinline__ uint4 ld_rlx128(const uint4* p) { uint4 v; asm volatile("ld.relaxed.gpu.global.v4.u32 {%0,%1,%2,%3}, [%4];" : "=r"(v.x), "=r"(v.y), "=r"(v.z), "=r"(v.w) : "l"(p) : "memory"); return v; }
__device__ __forceinline__ void st_rlx128z(uint4* p) { asm volatile("st.relaxed.gpu.global.v4.u32 [%0], {%1,%1,%1,%1};" ::"l"(p), "r"(0u) : "memory"); }

__device__ __forceinline__ float bf_lo(uint32_t u) { return __uint_as_float(u << 16); }
__device__ __forceinline__ float bf_hi(uint32_t u) { return __uint_as_float(u & 0xffff0000u); }
__device__ __forceinline__ uint32_t pack2(float lo, float hi) { uint32_t r; asm("cvt.rn.bf16x2.f32 %0, %1, %2;" : "=r"(r) : "f"(hi), "f"(lo)); return r; }
__device__ __forceinline__ float bfr(float v) { return __uint_as_float(pack2(0.f, v)); }
__device__ __forceinline__ uint32_t enc(float v) { uint32_t u = __float_as_uint(v); return u == 0u ? 0x80000000u : u; }
__device__ __forceinline__ float shx(float v, int o) { return __shfl_xor_sync(0xffffffffu, v, o); }

__device__ __forceinline__ void sts32_p(bool en, uint32_t a, uint32_t v) {
    asm volatile("{\n.reg .pred p;\nsetp.ne.u32 p, %2, 0;\n@p st.shared.u32 [%0], %1;\n}" ::"r"(a), "r"(v), "r"((uint32_t)en) : "memory");
}
__device__ __forceinline__ void sts64_p(bool en, uint32_t a, uint32_t x, uint32_t y) {
    asm volatile("{\n.reg .pred p;\nsetp.ne.u32 p, %3, 0;\n@p st.shared.v2.u32 [%0], {%1,%2};\n}" ::"r"(a), "r"(x), "r"(y), "r"((uint32_t)en) : "memory");
}
__device__ __forceinline__ void sts128f(uint32_t a, float x, float y, float z, float w) { asm volatile("st.shared.v4.f32 [%0], {%1,%2,%3,%4};" ::"r"(a), "f"(x), "f"(y), "f"(z), "f"(w) : "memory"); }
__device__ __forceinline__ void st_rlx_p(bool en, uint32_t* p, uint32_t v) {
    asm volatile("{\n.reg .pred p;\nsetp.ne.u32 p, %2, 0;\n@p st.relaxed.gpu.global.u32 [%0], %1;\n}" ::"l"(p), "r"(v), "r"((uint32_t)en) : "memory");
}
__device__ __forceinline__ void mbar_arrive_p(bool en, uint32_t a) {
    asm volatile("{\n.reg .pred p;\nsetp.ne.u32 p, %1, 0;\n@p mbarrier.arrive.shared::cta.b64 _, [%0];\n}" ::"r"(a), "r"((uint32_t)en) : "memory");
}
__device__ __forceinline__ void bar_comp_p(bool en, int id) {
    asm volatile("{\n.reg .pred p;\nsetp.ne.u32 p, %1, 0;\n@p bar.sync %0, 288;\n}" ::"r"(id), "r"((uint32_t)en) : "memory");
}
__device__ __forceinline__ uint32_t lop_ne(uint32_t a, uint32_t b, uint32_t c) { uint32_t r; asm("lop3.b32 %0, %1, %2, %3, 0x7E;" : "=r"(r) : "r"(a), "r"(b), "r"(c)); return r; }
__device__ __forceinline__ uint32_t stale(const uint4& v, uint32_t tg) { return (lop_ne(v.x, v.y, tg) | lop_ne(v.z, v.w, tg)) & 1u; }
__device__ __forceinline__ float selp(float a, float b, uint32_t c) { float r; asm("{\n.reg .pred p;\nsetp.ne.u32 p, %3, 0;\nselp.f32 %0, %1, %2, p;\n}" : "=f"(r) : "f"(a), "f"(b), "r"(c)); return r; }
__device__ __forceinline__ float sel4(float a0, float a1, float a2, float a3, uint32_t i) { return selp(selp(a3, a2, i & 1), selp(a1, a0, i & 1), i & 2); }
#define F2U __float_as_uint
#define U2F __uint_as_float

__global__ void __launch_bounds__(NTHREADS, 1)
fused_decode_kernel(const uint32_t* __restrict__ x32, const uint8_t* __restrict__ kc, const uint8_t* __restrict__ vc,
                    uint32_t* __restrict__ out32, Scratch* sc_, const __grid_constant__ Maps maps) {
    extern __shared__ __align__(1024) uint8_t smem[];
    const uint32_t sb = s2u(smem);
    const int lane = threadIdx.x & 31, wid = threadIdx.x >> 5;
    const int b = blockIdx.x, h = b >> 3, s = b & 7;
    const bool is_main = b < NMAIN;
    const uint32_t full = sb + OFF_FULL, empty = sb + OFF_EMPTY;
    const uint32_t bar_q = sb + OFF_FULL + 26 * 8, bar_o = bar_q + 8;
    const int rot = ROT ? (b >> 2) & 3 : 0;
    const int crot = KVROT == 1 ? h : KVROT == 2 ? h >> 1 : 0;
    const size_t kvoff = ((size_t)h * SK + (SK - WIN) + s * (KVIL ? 64 : 512)) * 256;

    if (wid == 9) {
        const uint32_t t_start = gtime32();
        if (lane == 0) {
            mbar_init(full, 1);
            mbar_init(full + 24 * 8, 1);
            mbar_init(full + 25 * 8, 1);
            if (is_main) {
                mbar_expect(full, KV_BYTES);
                bulk_ld(sb, kc + kvoff + (crot & 7) * (KVIL ? 8 * KV_BYTES : KV_BYTES), KV_BYTES, full);
#pragma unroll
                for (int i = 0; i < 2; i++) {
                    mbar_expect(full + (24 + i) * 8, IT_BYTES);
                    tma2d_ld(sb + WQ_OFF + i * IT_BYTES, &maps.m[4], b * 32, ((rot + 2 * i) & 3) * 144, full + (24 + i) * 8);
                    tma2d_ld(sb + WQ_OFF + i * IT_BYTES + 9216, &maps.m[4], b * 32, ((rot + 2 * i + 1) & 3) * 144, full + (24 + i) * 8);
                }
                STAMP(18);
            }
#pragma unroll
            for (int i = 1; i < 24; i++) mbar_init(full + i * 8, 1);
            mbar_init(bar_q, 32);
            mbar_init(bar_o, 32);
            const uint32_t cnt = is_main ? 8 : 9;
#pragma unroll
            for (int i = 0; i < 12; i++) mbar_init(empty + i * 8, cnt);
            mbar_init(empty + 12 * 8, 9);
        }
        __syncwarp();
        asm volatile("bar.arrive 15, %0;" ::"n"(NTHREADS) : "memory");
        {
            const int i = lane;
            const int j = is_main ? i - 16 : i % 6;
            const int unit = is_main ? b : NMAIN + (b - NMAIN) * 4 + i / 6;
            const uint32_t off = is_main ? (i < 12 ? i * KV_BYTES : i < 16 ? (i - 12) * KV_BYTES : 65536u + (i - 16) * IT_BYTES) : (i % 11) * IT_BYTES;
            const int dep = is_main ? (i < 10 ? -1 : i < 12 ? 12 : i < 16 ? i - 12 : min(i - 11, 11)) : i - 11;
            int prev = i - (i >= LATE_FROM ? LATE_DEPTH : DEPTH);
            if (is_main && prev <= 0) prev = prev == 0 ? 25 : prev == -1 ? 0 : -1;
            const uint8_t* src = (i < 8 ? kc : vc) + kvoff + ((i + crot) & 7) * (KVIL ? 8 * KV_BYTES : KV_BYTES);
            const CUtensorMap* mp = &maps.m[j < 4 ? 0 : j >> 1];
            const int c0 = j < 4 ? unit * 32 : 0, c1 = j < 4 ? ((j + rot) & 3) * 144 : unit * 288 + (j & 1) * 144;
            const uint32_t dst = sb + off, bar = full + i * 8;
            const int i0 = is_main ? 1 : 0;
            const int cum = is_main ? 2 * IT_BYTES + (i < 16 ? i * KV_BYTES : 16 * KV_BYTES + (i - 16) * IT_BYTES) : i * IT_BYTES;
            const int t_rel = (cum - PACE_W0 + (PACE_STAGGER == 1 ? (b * 37 % 132) * (17000 / 132) : PACE_STAGGER == 2 ? (h * 7 % 17) * 1000 : PACE_STAGGER == 3 ? b * (17000 / 132) : 8500)) * PACE_PS_PER_B / 1000;
            if (i >= i0 && i < 24) mbar_expect(bar, j < 0 ? KV_BYTES : IT_BYTES);
            if (lane >= 28) asm volatile("prefetch.tensormap [%0];" ::"l"(&maps.m[lane & 3]) : "memory");
#pragma unroll 1
            for (int k = i0; k < 24; k++) {
                if (lane == k) {
                    if (prev >= 0) mbar_wait(full + prev * 8);
                    if (dep >= 0) mbar_wait(empty + dep * 8);
                    while ((int)(gtime32() - t_start) < t_rel) {}
                    if (j < 0) {
                        bulk_ld(dst, src, KV_BYTES, bar);
                    } else {
                        tma2d_ld(dst, mp, c0, c1, bar);
                        if (j < 4) tma2d_ld(dst + 9216, mp + 1, c0, c1, bar);
                    }
                }
                __syncwarp();
            }
        }
        return;
    }
    if (wid == 10) {
        asm volatile("bar.sync 15, %0;" ::"n"(NTHREADS) : "memory");
        if (!is_main) return;
        const uint32_t tg = ~lds32(sb + OFF_EP) & 1u;
        uint32_t n = 0;
        {
            if (!QEARLY) mbar_wait(full + QPOLL_FROM * 8);
            uint4 a, c;
            for (;;) {
                a = ld_rlx128(&g_q[h][lane * 2]);
                c = ld_rlx128(&g_q[h][lane * 2 + 1]);
                if (!__any_sync(0xffffffffu, stale(a, tg) | stale(c, tg))) break;
                if (++n > SPIN_LIMIT) __trap();
                if (QEARLY) mbar_wait(full + QPOLL_FROM * 8);
                __nanosleep(100);
            }
            asm volatile("st.shared.v4.u32 [%0], {%1,%2,%3,%4};" ::"r"(sb + OFF_Q + lane * 16), "r"(__byte_perm(a.x, a.y, 0x7632)), "r"(__byte_perm(a.z, a.w, 0x7632)),
                         "r"(__byte_perm(c.x, c.y, 0x7632)), "r"(__byte_perm(c.z, c.w, 0x7632)) : "memory");
            mbar_arrive_p(true, bar_q);
        }
        {
            const uint32_t* slot = &g_opart[h][s][lane];
            mbar_wait(full + (OEARLY ? OEARLY : OPOLL_FROM) * 8);
            uint32_t ov[8];
            for (;;) {
                uint32_t bad = 0;
#pragma unroll
                for (int i = 0; i < 8; i++) { ov[i] = ld_rlx(slot + i * 32); bad |= ov[i] ^ tg; }
                if (__all_sync(0xffffffffu, !(bad & 1u))) break;
                if (++n > SPIN_LIMIT) __trap();
                if (OEARLY) mbar_wait(full + OPOLL_FROM * 8);
                __nanosleep(OPOLL_SLEEP);
            }
            float lse[8], M = -INFINITY;
#pragma unroll
            for (int i = 0; i < 8; i++) { lse[i] = U2F(__ballot_sync(0xffffffffu, ov[i] & 2u)); M = fmaxf(M, lse[i]); }
            float o = 0.f, L = 0.f;
#pragma unroll
            for (int i = 0; i < 8; i++) {
                const float e = __expf(lse[i] - M);
                o = fmaf(e, U2F(ov[i]), o);
                L += e;
            }
            o = __fdividef(o, L);
            sts32_p(true, sb + OFF_OEX + lane * 4, pack2(o, __shfl_down_sync(0xffffffffu, o, 1)));
            mbar_arrive_p(true, bar_o);
        }
        return;
    }

    const int w = wid, t = threadIdx.x;
    const int g = lane >> 2, tq = lane & 3;
    float xres;
    {
        const uint32_t xr = ldg_nc32(x32 + (b < NRED ? b : 0) * 4 + (lane >> 1 & 3));
        xres = (lane & 1) ? bf_hi(xr) : bf_lo(xr);
        uint32_t xa[9];
#pragma unroll
        for (int i = 0; i < 9; i++) xa[i] = ldg_nc32(x32 + i * 32 + lane);
        const uint32_t xmine = ldg_nc32(x32 + t);
        if (t == 0) sts32_p(true, sb + OFF_EP, ld_rlx(&sc_->epoch));
        float sum = 0.f;
#pragma unroll
        for (int i = 0; i < 9; i++) sum += bf_lo(xa[i]) + bf_hi(xa[i]);
#pragma unroll
        for (int o = 16; o; o >>= 1) sum += shx(sum, o);
        const float mean = sum * (1.0f / D_MODEL);
        float sq = 0.f;
#pragma unroll
        for (int i = 0; i < 9; i++) { float a = bf_lo(xa[i]) - mean, c = bf_hi(xa[i]) - mean; sq = fmaf(a, a, fmaf(c, c, sq)); }
#pragma unroll
        for (int o = 16; o; o >>= 1) sq += shx(sq, o);
        const float m_bf = bfr(mean);
        const float sd = bfr(sqrtf(bfr(bfr(sq * (1.0f / D_MODEL)) + 1e-5f)));
        sts32_p(true, sb + OFF_XN + t * 4, pack2(bfr(bf_lo(xmine) - m_bf) / sd, bfr(bf_hi(xmine) - m_bf) / sd));
        STAMP0(1);
        asm volatile("bar.sync 15, %0;" ::"n"(NTHREADS) : "memory");
    }

    const uint32_t ep = lds32(sb + OFF_EP), tg = ~ep & 1u;
    uint32_t* outp = reinterpret_cast<uint32_t*>(&g_outpart[w * 8 + tq * 2][b * 2]) + g;
    const uint4* slot = &g_outpart[b < NRED ? b : 0][min(t, NCTA * 2 - 1)];
    asm volatile("" : "+l"(outp));
    asm volatile("" : "+l"(slot));
    uint4 fv = make_uint4(ep, ep, ep, ep);
    float acc[4][4];
#pragma unroll
    for (int i = 0; i < 4; i++) { acc[i][0] = 0.f; acc[i][1] = 0.f; acc[i][2] = 0.f; acc[i][3] = 0.f; }
    const int lrow = (lane >> 4) * 8 + (lane & 7), lc = lane >> 3 & 1;
    const uint32_t gu0 = sb + (w * 16 + lrow) * 64 + (lc ^ (lrow >> 1 & 3)) * 16;
    const uint32_t rwb = sb + (lrow * 9 + w) * 128, rwx = (lc ^ ((lrow + w) & 7)) * 16;
    uint32_t rw[4];
#pragma unroll
    for (int i = 0; i < 4; i++) rw[i] = rwb + ((i * 32) ^ rwx);
    const uint32_t xaddr = sb + OFF_XN + w * 32 + tq * 4;

    auto col_item = [&](float (&ga)[4][4], uint32_t off, uint32_t bar, int ra, int rb) {
        const uint32_t xA = xaddr + (ra & 3) * 288, xB = xaddr + (rb & 3) * 288;
        const uint32_t b0 = lds32(xA), b1 = lds32(xA + 16), b2 = lds32(xB), b3 = lds32(xB + 16);
        mbar_wait(bar);
#pragma unroll
        for (int i = 0; i < 4; i++) {
            const uint4 a = ldsm4t((gu0 ^ ((i & 1) * 32)) + off + (i >> 1) * 9216);
            mma16(ga[i], a.x, a.y, a.z, a.w, i < 2 ? b0 : b2, i < 2 ? b1 : b3);
        }
    };
    auto col_reduce = [&](float (&ga)[4][4], uint32_t red, float& gg, float& uu) {
        const float v0 = sel4(ga[0][0], ga[1][0], ga[2][0], ga[3][0], tq), v1 = sel4(ga[0][2], ga[1][2], ga[2][2], ga[3][2], tq);
        sts32_p(true, red + w * 256 + tq * 64 + g * 4, F2U(v0));
        sts32_p(true, red + w * 256 + tq * 64 + g * 4 + 32, F2U(v1));
        bar_comp_p(true, 3);
        gg = 0.f; uu = 0.f;
#pragma unroll
        for (int k = 0; k < 9; k++) { gg += lds32f(red + k * 256 + lane * 4); uu += lds32f(red + k * 256 + 128 + lane * 4); }
    };
    auto geglu = [&](float gg, float uu) {
        gg = bfr(gg); uu = bfr(uu);
        const float inner = 0.7978845608028654f * (gg + 0.044715f * gg * gg * gg);
        const float hv = bfr(__fdividef(gg, 1.0f + __expf(-2.0f * inner))) * uu;
        return pack2(hv, __shfl_down_sync(0xffffffffu, hv, 1));
    };
    auto row_item = [&](uint32_t off, uint32_t bar, uint32_t cp, int r0) {
        const uint32_t b0 = __shfl_sync(0xffffffffu, cp, r0 + tq * 2), b1 = __shfl_sync(0xffffffffu, cp, r0 + tq * 2 + 8);
        mbar_wait(bar);
#pragma unroll
        for (int i = 0; i < 4; i++) {
            const uint4 a = ldsm4t(rw[i] + off);
            mma16(acc[i], a.x, a.y, a.z, a.w, b0, b1);
        }
    };
#define ZERO44(A) _Pragma("unroll") for (int i_ = 0; i_ < 4; i_++) { A[i_][0] = 0.f; A[i_][1] = 0.f; A[i_][2] = 0.f; A[i_][3] = 0.f; }

    if (is_main) {
        float ga[4][4], gg, uu;
        ZERO44(ga)
        col_item(ga, WQ_OFF, full + 24 * 8, rot, rot + 1);
        col_item(ga, WQ_OFF + IT_BYTES, full + 25 * 8, rot + 2, rot + 3);
        mbar_arrive_p(lane == 0, empty + 12 * 8);
        STAMP0(19);
        col_reduce(ga, sb + OFF_RED, gg, uu);
        st_rlx_p(w == 8, reinterpret_cast<uint32_t*>(&g_q[h][s * 8]) + lane, pack2(0.f, gg + uu) | tg);
        STAMP0(2);
        if (w < 8) {
            mbar_wait(bar_q);
            STAMP0(3);
            uint4 qf[4];
#pragma unroll
            for (int j = 0; j < 4; j++) qf[j] = lds128(sb + OFF_Q + (g & 1) * 256 + ((j ^ (g >> 1 & 1)) * 4 + tq) * 16);
            const uint32_t koff = sb + (w * 8 + g) * 256 + tq * 16;
            const uint32_t kx = (g & 1) * 64;
            const uint32_t sw = sb + OFF_S + w * 512, pw = sb + OFF_P + w * 256;
            float m = -INFINITY;
#pragma unroll 2
            for (int c = 0; c < 8; c++) {
                mbar_wait(full + c * 8);
                uint4 kv[4];
#pragma unroll
                for (int j = 0; j < 4; j++) kv[j] = lds128(koff + c * KV_BYTES + ((j * 64) ^ kx));
                float c0[4] = {0.f, 0.f, 0.f, 0.f}, c1[4] = {0.f, 0.f, 0.f, 0.f};
#pragma unroll
                for (int j = 0; j < 4; j++) {
                    mma16(c0, qf[j].x, qf[j].x, qf[j].y, qf[j].y, kv[j].x, kv[j].y);
                    mma16(c1, qf[j].z, qf[j].z, qf[j].w, qf[j].w, kv[j].z, kv[j].w);
                }
                mbar_arrive_p(lane == 0, empty + c * 8);
                const float raw = (g & 2) ? c0[1] + c1[1] : c0[0] + c1[0];
                const float sc = bfr(bfr(raw) * 0.08838834764831845f);
                m = fmaxf(m, sc);
                sts32_p(g < 4, sw + c * 64 + (g & 1) * 32 + tq * 8 + (g & 2) * 2, F2U(sc));
            }
            STAMP0(4);
            m = fmaxf(m, shx(m, 1)); m = fmaxf(m, shx(m, 2)); m = fmaxf(m, shx(m, 8));
            __syncwarp();
            {
                const float mh = __shfl_sync(0xffffffffu, m, (lane & 2) * 2);
                const float4 sv = lds128f(sw + lane * 16);
                const uint32_t p01 = pack2(__expf(sv.x - mh), __expf(sv.y - mh)), p23 = pack2(__expf(sv.z - mh), __expf(sv.w - mh));
                sts64_p(true, pw + lane * 8, p01, p23);
                float l = (bf_lo(p01) + bf_hi(p01)) + (bf_lo(p23) + bf_hi(p23));
                l += shx(l, 1); l += shx(l, 4); l += shx(l, 8); l += shx(l, 16);
                sts64_p((lane & 29) == 0, sb + OFF_ML + (lane >> 1) * 64 + w * 8, F2U(mh), F2U(l));
            }
            __syncwarp();
            float oc[8][4];
#pragma unroll
            for (int i = 0; i < 8; i++) { oc[i][0] = 0.f; oc[i][1] = 0.f; oc[i][2] = 0.f; oc[i][3] = 0.f; }
            const uint32_t voff = sb + (w * 8 + (lane & 7)) * 256;
            const uint32_t vx = ((lane >> 3) ^ (lane & 6)) * 16;
#pragma unroll 1
            for (int c = 0; c < 8; c++) {
                uint32_t pb = lds32(pw + c * 32 + (g & 1) * 16 + tq * 4);
                pb = (g >> 1) == tq ? pb : 0u;
                mbar_wait(full + (8 + c) * 8);
                const uint32_t vb = voff + (c < 4 ? c + 8 : c - 4) * KV_BYTES;
#pragma unroll
                for (int j = 0; j < 4; j++) {
                    const uint4 a = ldsm4t(vb + ((j * 64) ^ vx));
                    mma8(oc[2 * j], a.x, a.y, pb);
                    mma8(oc[2 * j + 1], a.z, a.w, pb);
                }
                mbar_arrive_p(lane == 0 && c < 4, empty + (8 + c) * 8);
            }
#pragma unroll
            for (int i = 0; i < 8; i += 2)
#pragma unroll
                for (int e = 0; e < 4; e++) oc[i][e] += shx(oc[i + 1][e], 1);
#pragma unroll
            for (int i = 0; i < 8; i += 4)
#pragma unroll
                for (int e = 0; e < 4; e++) {
                    oc[i][e] += shx(oc[i + 2][e], 2);
                    sts32_p(true, sb + OFF_RED + w * 1024 + (e & 1) * 512 + ((2 * i + (e >> 1)) ^ (2 * tq)) * 32 + g * 4, F2U(oc[i][e]));
                }
        }
        STAMP0(5);
        bar_comp_p(true, 2);
        if (w < 8) {
            const uint32_t ml = sb + OFF_ML + (t >> 7) * 64;
            float mm[8], ll[8];
#pragma unroll
            for (int i = 0; i < 4; i++) { float4 a = lds128f(ml + i * 16); mm[2 * i] = a.x; ll[2 * i] = a.y; mm[2 * i + 1] = a.z; ll[2 * i + 1] = a.w; }
            float M = mm[0];
#pragma unroll
            for (int i = 1; i < 8; i++) M = fmaxf(M, mm[i]);
            float o = 0.f, L = 0.f;
#pragma unroll
            for (int i = 0; i < 8; i++) {
                float e = __expf(mm[i] - M);
                o = fmaf(e, lds32f(sb + OFF_RED + i * 1024 + t * 4), o);
                L = fmaf(e, ll[i], L);
            }
            const uint32_t lse = F2U(M + __logf(L));
            st_rlx_p(true, &g_opart[h][w][s * 32 + lane], (F2U(__fdividef(o, L)) & ~3u) | ((lse >> lane & 1u) << 1) | tg);
        }
        STAMP0(6);
        ZERO44(ga)
#pragma unroll
        for (int j = 0; j < 4; j++) col_item(ga, 65536u + j * IT_BYTES, full + (16 + j) * 8, rot + j, rot + j);
        STAMP0(7);
        if (b < NRED && FPOLL_AT == 0) fv = ld_rlx128(slot);
        col_reduce(ga, sb + OFF_S, gg, uu);
        const uint32_t hp = geglu(gg, uu);
        row_item(65536u + 4 * IT_BYTES, full + 20 * 8, hp, 0);
        if (b < NRED && FPOLL_AT == 1) fv = ld_rlx128(slot);
        row_item(65536u + 5 * IT_BYTES, full + 21 * 8, hp, 16);
        if (b < NRED && FPOLL_AT == 2) fv = ld_rlx128(slot);
        STAMP0(9);
        mbar_wait(bar_o);
        const uint32_t op = lds32(sb + OFF_OEX + lane * 4);
        row_item(65536u + 6 * IT_BYTES, full + 22 * 8, op, 0);
        STAMP0(10);
        row_item(65536u + 7 * IT_BYTES, full + 23 * 8, op, 16);
    } else {
        int it = 0;
        uint32_t off = 0;
#pragma unroll 1
        for (int u = 0; u < 4; u++) {
            float ga[4][4], gg, uu;
            ZERO44(ga)
#pragma unroll 1
            for (int j = 0; j < 4; j++) {
                col_item(ga, off, full + it * 8, rot + j, rot + j);
                mbar_arrive_p(lane == 0 && it < 13, empty + it * 8);
                it++; off = off == 10 * IT_BYTES ? 0u : off + IT_BYTES;
            }
            col_reduce(ga, sb + OFF_RED + (u & 1) * 2304, gg, uu);
            const uint32_t hp = geglu(gg, uu);
#pragma unroll 1
            for (int j = 0; j < 2; j++) {
                row_item(off, full + it * 8, hp, j * 16);
                mbar_arrive_p(lane == 0 && it < 13, empty + it * 8);
                it++; off = off == 10 * IT_BYTES ? 0u : off + IT_BYTES;
            }
        }
    }
    {
        const float v0 = sel4(acc[0][0], acc[1][0], acc[2][0], acc[3][0], tq), v1 = sel4(acc[0][2], acc[1][2], acc[2][2], acc[3][2], tq);
        st_rlx_p(true, outp, (F2U(v0) & ~1u) | tg);
        st_rlx_p(true, outp + NCTA * 8, (F2U(v1) & ~1u) | tg);
    }
    STAMP0(11);
    if (b < NRED) {
        for (uint32_t n = 0; stale(fv, tg); n++) {
            fv = ld_rlx128(slot);
            if (n > SPIN_LIMIT) __trap();
        }
        __syncwarp();
        if (t >= NCTA * 2) fv = make_uint4(0u, 0u, 0u, 0u);
        const bool b2 = lane & 2, b4 = lane & 4;
        const float k0 = U2F(b2 ? fv.z : fv.x) + shx(U2F(b2 ? fv.x : fv.z), 2);
        const float k1 = U2F(b2 ? fv.w : fv.y) + shx(U2F(b2 ? fv.y : fv.w), 2);
        float k = (b4 ? k1 : k0) + shx(b4 ? k0 : k1, 4);
        k += shx(k, 8);
        k += shx(k, 16);
        sts32_p(lane < 8, sb + OFF_FIN + ((lane & 1) * 4 + (lane & 2) + (lane >> 2 & 1)) * 48 + w * 4, F2U(k));
        if (w == 0) {
            asm volatile("bar.sync 4, 288;" ::: "memory");
            const uint32_t fa = sb + OFF_FIN + (lane & 7) * 48;
            const float4 p0 = lds128f(fa), p1 = lds128f(fa + 16);
            const float r = (((p0.x + p0.y) + (p0.z + p0.w)) + ((p1.x + p1.y) + (p1.z + p1.w))) + (lds32f(fa + 32) + xres);
            const uint32_t o2 = pack2(r, __shfl_down_sync(0xffffffffu, r, 1));
            if ((lane & 25) == 0) out32[b * 4 + (lane >> 1)] = o2;
            if (b == 0 && lane == 0) sc_->epoch = ep + 1;
            STAMP0(12);
        } else {
            asm volatile("bar.arrive 4, 288;" ::: "memory");
        }
    }
}

typedef CUresult (*EncodeFn)(CUtensorMap*, CUtensorMapDataType, cuuint32_t, void*, const cuuint64_t*, const cuuint64_t*,
                             const cuuint32_t*, const cuuint32_t*, CUtensorMapInterleave, CUtensorMapSwizzle,
                             CUtensorMapL2promotion, CUtensorMapFloatOOBfill);

void make_map(EncodeFn fn, CUtensorMap* m, const void* p, int inner, int outer, int box_inner, CUtensorMapSwizzle sw) {
    cuuint64_t gd[2] = {(cuuint64_t)inner, (cuuint64_t)outer};
    cuuint64_t gs[1] = {(cuuint64_t)inner * 2};
    cuuint32_t bd[2] = {(cuuint32_t)box_inner, 144};
    cuuint32_t es[2] = {1, 1};
    fn(m, CU_TENSOR_MAP_DATA_TYPE_BFLOAT16, 2, const_cast<void*>(p), gd, gs, bd, es, CU_TENSOR_MAP_INTERLEAVE_NONE,
       sw, (CUtensorMapL2promotion)PROMO, CU_TENSOR_MAP_FLOAT_OOB_FILL_NONE);
}

}

extern "C" void kernel_launch(void* const* d_in, const int* in_sizes, int n_in, void* d_out, int out_size) {
    (void)in_sizes; (void)n_in; (void)out_size;
    static EncodeFn enc_fn = nullptr;
    static void* scratch = nullptr;
    if (!enc_fn) {
        cudaDriverEntryPointQueryResult qr;
        void* fn = nullptr;
        cudaGetDriverEntryPoint("cuTensorMapEncodeTiled", &fn, cudaEnableDefault, &qr);
        enc_fn = (EncodeFn)fn;
        cudaGetSymbolAddress(&scratch, g_scratch);
        cudaFuncSetAttribute(fused_decode_kernel, cudaFuncAttributeMaxDynamicSharedMemorySize, SMEM_BYTES);
    }
    Maps maps;
    make_map(enc_fn, &maps.m[0], d_in[6], FF, D_MODEL, 32, CU_TENSOR_MAP_SWIZZLE_64B);
    make_map(enc_fn, &maps.m[1], d_in[7], FF, D_MODEL, 32, CU_TENSOR_MAP_SWIZZLE_64B);
    make_map(enc_fn, &maps.m[2], d_in[8], 64, FF * 9, 64, CU_TENSOR_MAP_SWIZZLE_128B);
    make_map(enc_fn, &maps.m[3], d_in[4], 64, NQ * 9, 64, CU_TENSOR_MAP_SWIZZLE_128B);
    make_map(enc_fn, &maps.m[4], d_in[3], NQ, D_MODEL, 32, CU_TENSOR_MAP_SWIZZLE_64B);
    fused_decode_kernel<<<NCTA, NTHREADS, SMEM_BYTES>>>(
        (const uint32_t*)d_in[0], (const uint8_t*)d_in[1], (const uint8_t*)d_in[2],
        (uint32_t*)d_out, (Scratch*)scratch, maps);
}
```

```cpp
#include <cuda_runtime.h>
#include <cuda_bf16.h>
#include <cuda.h>
#include <stdint.h>

namespace {

constexpr int D_MODEL = 576;
constexpr int SK = 65536;
constexpr int WIN = 4096;
constexpr int NQ = 4096;
constexpr int FF = 4608;
constexpr int NMAIN = 128;
constexpr int NCTA = 132;
constexpr int NRED = 36;
constexpr int NTHREADS = 352;
#define PACE_W0 20000
#define PACE_NS 0.041f
#define C_AT 17700
#define NOINIT 1
#define P_AT 0
#define PSLEEP 0
#define STAG 128
#define SORD 0
#define OPOLL_FROM 17
#define QPOLL_FROM 3
#define DEPTH 6

constexpr uint32_t KV_BYTES = 16384;
constexpr uint32_t IT_BYTES = 18432;
constexpr uint32_t WQ_OFF = 176128;
constexpr uint32_t MISC_OFF = 212992;
constexpr uint32_t OFF_FULL = MISC_OFF;
constexpr uint32_t OFF_EMPTY = MISC_OFF + 256;
constexpr uint32_t OFF_XN = MISC_OFF + 512;
constexpr uint32_t OFF_RED = OFF_XN + 1152;
constexpr uint32_t OFF_Q = OFF_RED + 9216;
constexpr uint32_t OFF_S = OFF_Q + 512;
constexpr uint32_t OFF_P = OFF_S + 4096;
constexpr uint32_t OFF_OEX = OFF_P + 2048;
constexpr uint32_t OFF_ML = OFF_OEX + 128;
constexpr uint32_t OFF_EP = OFF_ML + 128;
constexpr uint32_t OFF_FIN = OFF_P;
constexpr uint32_t SMEM_BYTES = OFF_EP + 16;
static_assert(SMEM_BYTES <= 232448, "smem");

constexpr uint32_t SPIN_LIMIT = 1u << 22;

struct Scratch {
    uint4 q[16][64];
    uint32_t opart[16][8][8 * 32];
    uint4 hx[16][8];
    uint4 outpart[NRED][NMAIN * 4];
    uint32_t epoch;
};
__device__ __align__(128) Scratch g_scratch;

struct Maps { CUtensorMap m[6]; };

__device__ __forceinline__ uint32_t gtime32() { uint32_t t; asm volatile("mov.u32 %0, %globaltimer_lo;" : "=r"(t)); return t; }
#define STAMP(i)
#define STAMP0(i)

__device__ __forceinline__ uint32_t s2u(const void* p) { return (uint32_t)__cvta_generic_to_shared(p); }
__device__ __forceinline__ void mbar_init(uint32_t a, uint32_t c) { asm volatile("mbarrier.init.shared::cta.b64 [%0], %1;" ::"r"(a), "r"(c) : "memory"); }
__device__ __forceinline__ void mbar_expect(uint32_t a, uint32_t b) { asm volatile("mbarrier.arrive.expect_tx.shared::cta.b64 _, [%0], %1;" ::"r"(a), "r"(b) : "memory"); }
__device__ __forceinline__ void mbar_wait(uint32_t a) {
    uint32_t ok, n = 0;
    do {
        asm volatile("{\n.reg .pred p;\nmbarrier.try_wait.parity.shared::cta.b64 p, [%1], 0;\nselp.u32 %0, 1, 0, p;\n}" : "=r"(ok) : "r"(a) : "memory");
        if (++n > SPIN_LIMIT) __trap();
    } while (!ok);
}
__device__ __forceinline__ void bulk_ld(uint32_t dst, const void* src, uint32_t bytes, uint32_t bar) {
    asm volatile("cp.async.bulk.shared::cluster.global.mbarrier::complete_tx::bytes [%0], [%1], %2, [%3];" ::"r"(dst), "l"(src), "r"(bytes), "r"(bar) : "memory");
}
__device__ __forceinline__ void tma2d_ld(uint32_t dst, const CUtensorMap* m, int c0, int c1, uint32_t bar) {
    asm volatile("cp.async.bulk.tensor.2d.shared::cluster.global.mbarrier::complete_tx::bytes [%0], [%1, {%3, %4}], [%2];" ::"r"(dst), "l"(m), "r"(bar), "r"(c0), "r"(c1) : "memory");
}
__device__ __forceinline__ uint4 lds128(uint32_t a) { uint4 v; asm volatile("ld.shared.v4.u32 {%0,%1,%2,%3}, [%4];" : "=r"(v.x), "=r"(v.y), "=r"(v.z), "=r"(v.w) : "r"(a) : "memory"); return v; }
__device__ __forceinline__ float4 lds128f(uint32_t a) { float4 v; asm volatile("ld.shared.v4.f32 {%0,%1,%2,%3}, [%4];" : "=f"(v.x), "=f"(v.y), "=f"(v.z), "=f"(v.w) : "r"(a) : "memory"); return v; }
__device__ __forceinline__ uint32_t lds32(uint32_t a) { uint32_t v; asm volatile("ld.shared.u32 %0, [%1];" : "=r"(v) : "r"(a) : "memory"); return v; }
__device__ __forceinline__ float lds32f(uint32_t a) { float v; asm volatile("ld.shared.f32 %0, [%1];" : "=f"(v) : "r"(a) : "memory"); return v; }
__device__ __forceinline__ uint4 ldsm4t(uint32_t a) {
    uint4 v;
    asm volatile("ldmatrix.sync.aligned.m8n8.x4.trans.shared.b16 {%0,%1,%2,%3}, [%4];" : "=r"(v.x), "=r"(v.y), "=r"(v.z), "=r"(v.w) : "r"(a) : "memory");
    return v;
}
__device__ __forceinline__ void mma16(float (&c)[4], uint32_t a0, uint32_t a1, uint32_t a2, uint32_t a3, uint32_t b0, uint32_t b1) {
    asm volatile("mma.sync.aligned.m16n8k16.row.col.f32.bf16.bf16.f32 {%0,%1,%2,%3}, {%4,%5,%6,%7}, {%8,%9}, {%0,%1,%2,%3};"
                 : "+f"(c[0]), "+f"(c[1]), "+f"(c[2]), "+f"(c[3]) : "r"(a0), "r"(a1), "r"(a2), "r"(a3), "r"(b0), "r"(b1));
}
__device__ __forceinline__ void mma8(float (&c)[4], uint32_t a0, uint32_t a1, uint32_t b0) {
    asm volatile("mma.sync.aligned.m16n8k8.row.col.f32.bf16.bf16.f32 {%0,%1,%2,%3}, {%4,%5}, {%6}, {%0,%1,%2,%3};"
                 : "+f"(c[0]), "+f"(c[1]), "+f"(c[2]), "+f"(c[3]) : "r"(a0), "r"(a1), "r"(b0));
}
__device__ __forceinline__ uint32_t ldg_nc32(const void* p) { uint32_t v; asm volatile("ld.global.nc.u32 %0, [%1];" : "=r"(v) : "l"(p)); return v; }
__device__ __forceinline__ uint32_t ld_rlx(const uint32_t* p) { uint32_t v; asm volatile("ld.relaxed.gpu.global.u32 %0, [%1];" : "=r"(v) : "l"(p) : "memory"); return v; }
__device__ __forceinline__ uint4 ld_rlx128(const uint4* p) { uint4 v; asm volatile("ld.relaxed.gpu.global.v4.u32 {%0,%1,%2,%3}, [%4];" : "=r"(v.x), "=r"(v.y), "=r"(v.z), "=r"(v.w) : "l"(p) : "memory"); return v; }
__device__ __forceinline__ void ld_rlx128_p(uint4& v, const uint4* p, uint32_t en) {
    asm volatile("{\n.reg .pred p;\nsetp.ne.u32 p, %5, 0;\n@p ld.relaxed.gpu.global.v4.u32 {%0,%1,%2,%3}, [%4];\n}"
                 : "+r"(v.x), "+r"(v.y), "+r"(v.z), "+r"(v.w) : "l"(p), "r"(en) : "memory");
}
__device__ __forceinline__ void st_rlx64(uint32_t* p, uint32_t a, uint32_t b) { asm volatile("st.relaxed.gpu.global.v2.u32 [%0], {%1,%2};" ::"l"(p), "r"(a), "r"(b) : "memory"); }

__device__ __forceinline__ float bf_lo(uint32_t u) { return __uint_as_float(u << 16); }
__device__ __forceinline__ float bf_hi(uint32_t u) { return __uint_as_float(u & 0xffff0000u); }
__device__ __forceinline__ uint32_t pack2(float lo, float hi) { uint32_t r; asm("cvt.rn.bf16x2.f32 %0, %1, %2;" : "=r"(r) : "f"(hi), "f"(lo)); return r; }
__device__ __forceinline__ float bfr(float v) { return __uint_as_float(pack2(0.f, v)); }
__device__ __forceinline__ float shx(float v, int o) { return __shfl_xor_sync(0xffffffffu, v, o); }
__device__ __forceinline__ uint32_t hi2(uint32_t a, uint32_t b) { return __byte_perm(a, b, 0x7632); }

__device__ __forceinline__ void sts32_p(bool en, uint32_t a, uint32_t v) {
    asm volatile("{\n.reg .pred p;\nsetp.ne.u32 p, %2, 0;\n@p st.shared.u32 [%0], %1;\n}" ::"r"(a), "r"(v), "r"((uint32_t)en) : "memory");
}
__device__ __forceinline__ void sts64_p(bool en, uint32_t a, uint32_t x, uint32_t y) {
    asm volatile("{\n.reg .pred p;\nsetp.ne.u32 p, %3, 0;\n@p st.shared.v2.u32 [%0], {%1,%2};\n}" ::"r"(a), "r"(x), "r"(y), "r"((uint32_t)en) : "memory");
}
__device__ __forceinline__ void st_rlx_p(bool en, uint32_t* p, uint32_t v) {
    asm volatile("{\n.reg .pred p;\nsetp.ne.u32 p, %2, 0;\n@p st.relaxed.gpu.global.u32 [%0], %1;\n}" ::"l"(p), "r"(v), "r"((uint32_t)en) : "memory");
}
__device__ __forceinline__ void mbar_arrive_p(bool en, uint32_t a) {
    asm volatile("{\n.reg .pred p;\nsetp.ne.u32 p, %1, 0;\n@p mbarrier.arrive.shared::cta.b64 _, [%0];\n}" ::"r"(a), "r"((uint32_t)en) : "memory");
}
__device__ __forceinline__ uint32_t lop_ne(uint32_t a, uint32_t b, uint32_t c) { uint32_t r; asm("lop3.b32 %0, %1, %2, %3, 0x7E;" : "=r"(r) : "r"(a), "r"(b), "r"(c)); return r; }
__device__ __forceinline__ uint32_t stale(const uint4& v, uint32_t tg) { return (lop_ne(v.x, v.y, tg) | lop_ne(v.z, v.w, tg)) & 1u; }
__device__ __forceinline__ float selp(float a, float b, uint32_t c) { float r; asm("{\n.reg .pred p;\nsetp.ne.u32 p, %3, 0;\nselp.f32 %0, %1, %2, p;\n}" : "=f"(r) : "f"(a), "f"(b), "r"(c)); return r; }
__device__ __forceinline__ float sel4(float a0, float a1, float a2, float a3, uint32_t i) { return selp(selp(a3, a2, i & 1), selp(a1, a0, i & 1), i & 2); }
#define F2U __float_as_uint
#define U2F __uint_as_float
#define BAR_COMP(id) asm volatile("bar.sync " #id ", 288;" ::: "memory")
#define ZERO44(A) _Pragma("unroll") for (int i_ = 0; i_ < 4; i_++) { A[i_][0] = 0.f; A[i_][1] = 0.f; A[i_][2] = 0.f; A[i_][3] = 0.f; }

__global__ void __launch_bounds__(NTHREADS, 1)
fused_decode_kernel(const uint32_t* __restrict__ x32, const uint8_t* __restrict__ kc, const uint8_t* __restrict__ vc,
                    uint16_t* __restrict__ out16, Scratch* sc, const __grid_constant__ Maps maps) {
    extern __shared__ __align__(1024) uint8_t smem[];
    const uint32_t sb = s2u(smem);
    const int lane = threadIdx.x & 31, wid = threadIdx.x >> 5;
    const int b = blockIdx.x, h = b >> 3, s = b & 7;
    const bool is_main = b < NMAIN, is_red = b < NRED;
    const uint32_t full = sb + OFF_FULL, empty = sb + OFF_EMPTY;
    const uint32_t bar_q = sb + OFF_FULL + 27 * 8, bar_o = bar_q + 8;
    const size_t kvoff = ((size_t)h * SK + (SK - WIN) + s * 64) * 256;

    if (threadIdx.x == 0) {
        mbar_init(full, 1);
        if (is_main) {
            mbar_expect(full, KV_BYTES);
            bulk_ld(sb, kc + kvoff, KV_BYTES, full);
        }
    }
    if (threadIdx.x == 32 && is_main) {
#pragma unroll
        for (int i = 0; i < 2; i++) {
            mbar_init(full + (25 + i) * 8, 1);
            mbar_expect(full + (25 + i) * 8, IT_BYTES);
            tma2d_ld(sb + WQ_OFF + i * IT_BYTES, &maps.m[5], b * 32, i * 288, full + (25 + i) * 8);
            tma2d_ld(sb + WQ_OFF + i * IT_BYTES + 9216, &maps.m[5], b * 32, i * 288 + 144, full + (25 + i) * 8);
        }
        STAMP(18);
    }
    if (wid == 0) {
        const uint32_t t_start = gtime32() - 150;
        if (lane == 0) {
#pragma unroll
            for (int i = 1; i < 25; i++) mbar_init(full + i * 8, 1);
            mbar_init(bar_q, 32);
            mbar_init(bar_o, 32);
            const uint32_t cnt = is_main ? 8 : 9;
#pragma unroll
            for (int i = 0; i < 13; i++) mbar_init(empty + i * 8, cnt);
            mbar_init(empty + 13 * 8, 9);
        }
        __syncwarp();
        asm volatile("bar.arrive 15, %0;" ::"n"(NTHREADS) : "memory");
        const int i = lane;
        const int j = is_main ? i - 16 : i & 3;
        const int unit = is_main ? b : NMAIN + (b - NMAIN) * 4 + (i >> 2);
        const uint32_t off = !is_main ? (i % 11) * IT_BYTES : i < 12 ? i * KV_BYTES : i < 16 ? (i - 12) * KV_BYTES : i < 24 ? 65536u + (i - 16) * IT_BYTES : 0u;
        const int dep = is_main ? (i < 10 ? -1 : i < 12 ? 13 : i < 16 ? i - 12 : i < 24 ? min(i - 11, 11) : 12) : i - 11;
        const int prev = i - DEPTH;
        const uint8_t* src = (i < 8 ? kc : vc) + kvoff + (i & 7) * (8 * KV_BYTES);
        const CUtensorMap* mp = &maps.m[j < 4 ? 0 : min(j >> 1, 4)];
        const int c0 = j < 4 ? unit * 32 : j < 8 ? 0 : b * 16;
        const int c1 = j < 4 ? j * 144 : j < 8 ? unit * 288 + (j & 1) * 144 : NMAIN * 32;
        const uint32_t dst = sb + off, bar = full + i * 8;
        const int i0 = is_main ? 1 : 0, i1 = is_red ? 25 : is_main ? 24 : 16;
        const int cum = is_main ? 2 * IT_BYTES + (i < 16 ? i * KV_BYTES : 16 * KV_BYTES + (i - 16) * IT_BYTES) : i * IT_BYTES;
        const int t_rel = j == 8 ? C_AT : (int)((float)(cum - PACE_W0 + (SORD == 0 ? b * 37 % 132 : SORD == 1 ? b : 131 - b) * STAG) * PACE_NS);
        if (i >= i0 && i < i1) mbar_expect(bar, (j < 0 || j == 8) ? KV_BYTES : IT_BYTES);
        if (lane >= 27) asm volatile("prefetch.tensormap [%0];" ::"l"(&maps.m[lane - 27]) : "memory");
#pragma unroll 1
        for (int k = i0; k < i1; k++) {
            if (lane == k) {
                if (prev >= 0) mbar_wait(full + prev * 8);
                if (dep >= 0) mbar_wait(empty + dep * 8);
                while ((int)(gtime32() - t_start) < t_rel) {}
                if (j < 0) {
                    bulk_ld(dst, src, KV_BYTES, bar);
                } else {
                    tma2d_ld(dst, mp, c0, c1, bar);
                    if (j < 4) tma2d_ld(dst + 9216, mp + 1, c0, c1, bar);
                    if (j == 8) tma2d_ld(dst + 8192, mp, c0, c1 + 256, bar);
                }
            }
            __syncwarp();
        }
        return;
    }
    if (wid == 1) {
        asm volatile("bar.sync 15, %0;" ::"n"(NTHREADS) : "memory");
        if (!is_main) return;
        const uint32_t tg = ~lds32(sb + OFF_EP) & 1u;
        uint32_t n = 0;
        {
            mbar_wait(full + QPOLL_FROM * 8);
            uint4 a, c;
            for (;;) {
                a = ld_rlx128(&sc->q[h][lane * 2]);
                c = ld_rlx128(&sc->q[h][lane * 2 + 1]);
                if (!__any_sync(0xffffffffu, stale(a, tg) | stale(c, tg))) break;
                if (++n > SPIN_LIMIT) __trap();
                __nanosleep(100);
            }
            asm volatile("st.shared.v4.u32 [%0], {%1,%2,%3,%4};" ::"r"(sb + OFF_Q + lane * 16), "r"(hi2(a.x, a.y)), "r"(hi2(a.z, a.w)),
                         "r"(hi2(c.x, c.y)), "r"(hi2(c.z, c.w)) : "memory");
            mbar_arrive_p(true, bar_q);
        }
        {
            const uint32_t* slot = &sc->opart[h][s][lane];
            mbar_wait(full + OPOLL_FROM * 8);
            uint32_t ov[8];
            for (;;) {
                uint32_t bad = 0;
#pragma unroll
                for (int i = 0; i < 8; i++) { ov[i] = ld_rlx(slot + i * 32); bad |= ov[i] ^ tg; }
                if (__all_sync(0xffffffffu, !(bad & 1u))) break;
                if (++n > SPIN_LIMIT) __trap();
                __nanosleep(100);
            }
            float lse[8], M = -INFINITY;
#pragma unroll
            for (int i = 0; i < 8; i++) { lse[i] = U2F(__ballot_sync(0xffffffffu, ov[i] & 2u)); M = fmaxf(M, lse[i]); }
            float o = 0.f, L = 0.f;
#pragma unroll
            for (int i = 0; i < 8; i++) {
                const float e = __expf(lse[i] - M);
                o = fmaf(e, U2F(ov[i]), o);
                L += e;
            }
            o = __fdividef(o, L);
            sts32_p(true, sb + OFF_OEX + lane * 4, pack2(o, __shfl_down_sync(0xffffffffu, o, 1)));
            mbar_arrive_p(true, bar_o);
        }
        return;
    }

    const uint32_t t_cta = gtime32();
    const int w = wid - 2, t = threadIdx.x - 64;
    const int g = lane >> 2, tq = lane & 3;
    float xres;
    {
        const uint32_t xr = ldg_nc32(x32 + (is_red ? b : 0) * 8 + (lane >> 1 & 7));
        xres = (lane & 1) ? bf_hi(xr) : bf_lo(xr);
        uint32_t xa[9];
#pragma unroll
        for (int i = 0; i < 9; i++) xa[i] = ldg_nc32(x32 + i * 32 + lane);
        const uint32_t xmine = ldg_nc32(x32 + t);
        if (t == 0) sts32_p(true, sb + OFF_EP, ld_rlx(&sc->epoch));
        float sum = 0.f;
#pragma unroll
        for (int i = 0; i < 9; i++) sum += bf_lo(xa[i]) + bf_hi(xa[i]);
#pragma unroll
        for (int o = 16; o; o >>= 1) sum += shx(sum, o);
        const float mean = sum * (1.0f / D_MODEL);
        float sq = 0.f;
#pragma unroll
        for (int i = 0; i < 9; i++) { float a = bf_lo(xa[i]) - mean, c = bf_hi(xa[i]) - mean; sq = fmaf(a, a, fmaf(c, c, sq)); }
#pragma unroll
        for (int o = 16; o; o >>= 1) sq += shx(sq, o);
        const float m_bf = bfr(mean);
        const float sd = bfr(sqrtf(bfr(bfr(sq * (1.0f / D_MODEL)) + 1e-5f)));
        sts32_p(true, sb + OFF_XN + t * 4, pack2(bfr(bf_lo(xmine) - m_bf) / sd, bfr(bf_hi(xmine) - m_bf) / sd));
        STAMP0(1);
        asm volatile("bar.sync 15, %0;" ::"n"(NTHREADS) : "memory");
    }

    const uint32_t ep = lds32(sb + OFF_EP), tg = ~ep & 1u;
    const int lrow = (lane >> 4) * 8 + (lane & 7), lc = lane >> 3 & 1;
    const uint32_t gu0 = sb + (w * 16 + lrow) * 64 + (lc ^ (lrow >> 1 & 3)) * 16;
    const uint32_t xaddr = sb + OFF_XN + w * 32 + tq * 4;

    auto col_item = [&](float (&ga)[4][4], uint32_t off, uint32_t bar, int ra, int rb) {
        const uint32_t xA = xaddr + ra * 288, xB = xaddr + rb * 288;
        const uint32_t b0 = lds32(xA), b1 = lds32(xA + 16), b2 = lds32(xB), b3 = lds32(xB + 16);
        mbar_wait(bar);
#pragma unroll
        for (int i = 0; i < 4; i++) {
            const uint4 a = ldsm4t((gu0 ^ ((i & 1) * 32)) + off + (i >> 1) * 9216);
            mma16(ga[i], a.x, a.y, a.z, a.w, i < 2 ? b0 : b2, i < 2 ? b1 : b3);
        }
    };
    auto col_reduce = [&](float (&ga)[4][4], uint32_t red, float& gg, float& uu) {
        const float v0 = sel4(ga[0][0], ga[1][0], ga[2][0], ga[3][0], tq), v1 = sel4(ga[0][2], ga[1][2], ga[2][2], ga[3][2], tq);
        sts32_p(true, red + w * 256 + tq * 64 + g * 4, F2U(v0));
        sts32_p(true, red + w * 256 + tq * 64 + g * 4 + 32, F2U(v1));
        BAR_COMP(3);
        gg = 0.f; uu = 0.f;
#pragma unroll
        for (int k = 0; k < 9; k++) { gg += lds32f(red + k * 256 + lane * 4); uu += lds32f(red + k * 256 + 128 + lane * 4); }
    };
    auto geglu = [&](float gg, float uu) {
        gg = bfr(gg); uu = bfr(uu);
        const float inner = 0.7978845608028654f * (gg + 0.044715f * gg * gg * gg);
        const float hv = bfr(__fdividef(gg, 1.0f + __expf(-2.0f * inner))) * uu;
        return pack2(hv, __shfl_down_sync(0xffffffffu, hv, 1));
    };

    if (!is_main) {
        int it = 0;
        uint32_t off = 0;
#pragma unroll 1
        for (int u = 0; u < 4; u++) {
            float ga[4][4], gg, uu;
            ZERO44(ga)
#pragma unroll 1
            for (int j = 0; j < 4; j++) {
                col_item(ga, off, full + it * 8, j, j);
                mbar_arrive_p(lane == 0 && it < 5, empty + it * 8);
                it++; off = off == 10 * IT_BYTES ? 0u : off + IT_BYTES;
            }
            col_reduce(ga, sb + OFF_RED + (u & 1) * 2304, gg, uu);
            const uint32_t hp = geglu(gg, uu);
            st_rlx_p(w == 8, reinterpret_cast<uint32_t*>(&sc->hx[(b - NMAIN) * 4 + u][0]) + (lane >> 1 & 3) * 8 + (lane >> 3) * 2 + (lane & 1), hp << 16 | tg);
        }
        return;
    }

    uint32_t* outp = reinterpret_cast<uint32_t*>(&sc->outpart[w * 4 + tq][b * 4]) + g * 2;
    float ga[4][4], gg, uu;
    ZERO44(ga)
    col_item(ga, WQ_OFF, full + 25 * 8, 0, 1);
    col_item(ga, WQ_OFF + IT_BYTES, full + 26 * 8, 2, 3);
    mbar_arrive_p(lane == 0, empty + 13 * 8);
    STAMP0(19);
    col_reduce(ga, sb + OFF_RED, gg, uu);
    st_rlx_p(w == 8, reinterpret_cast<uint32_t*>(&sc->q[h][s * 8]) + lane, pack2(0.f, gg + uu) | tg);
    STAMP0(2);
    if (w < 8) {
        mbar_wait(bar_q);
        STAMP0(3);
        uint4 qf[4];
#pragma unroll
        for (int j = 0; j < 4; j++) qf[j] = lds128(sb + OFF_Q + (g & 1) * 256 + ((j ^ (g >> 1 & 1)) * 4 + tq) * 16);
        const uint32_t koff = sb + (w * 8 + g) * 256 + tq * 16;
        const uint32_t kx = (g & 1) * 64;
        const uint32_t sw = sb + OFF_S + w * 512, pw = sb + OFF_P + w * 256;
        float m = -INFINITY;
#pragma unroll 2
        for (int c = 0; c < 8; c++) {
            mbar_wait(full + c * 8);
            uint4 kv[4];
#pragma unroll
            for (int j = 0; j < 4; j++) kv[j] = lds128(koff + c * KV_BYTES + ((j * 64) ^ kx));
            float c0[4] = {0.f, 0.f, 0.f, 0.f}, c1[4] = {0.f, 0.f, 0.f, 0.f};
#pragma unroll
            for (int j = 0; j < 4; j++) {
                mma16(c0, qf[j].x, qf[j].x, qf[j].y, qf[j].y, kv[j].x, kv[j].y);
                mma16(c1, qf[j].z, qf[j].z, qf[j].w, qf[j].w, kv[j].z, kv[j].w);
            }
            mbar_arrive_p(lane == 0, empty + c * 8);
            const float raw = (g & 2) ? c0[1] + c1[1] : c0[0] + c1[0];
            const float scv = bfr(bfr(raw) * 0.08838834764831845f);
            m = fmaxf(m, scv);
            sts32_p(g < 4, sw + c * 64 + (g & 1) * 32 + tq * 8 + (g & 2) * 2, F2U(scv));
        }
        STAMP0(4);
        st_rlx_p(true, &sc->opart[h][w][s * 32 + lane], ep);
        m = fmaxf(m, shx(m, 1)); m = fmaxf(m, shx(m, 2)); m = fmaxf(m, shx(m, 8));
        __syncwarp();
        {
            const float mh = __shfl_sync(0xffffffffu, m, (lane & 2) * 2);
            const float4 sv = lds128f(sw + lane * 16);
            const uint32_t p01 = pack2(__expf(sv.x - mh), __expf(sv.y - mh)), p23 = pack2(__expf(sv.z - mh), __expf(sv.w - mh));
            sts64_p(true, pw + lane * 8, p01, p23);
            float l = (bf_lo(p01) + bf_hi(p01)) + (bf_lo(p23) + bf_hi(p23));
            l += shx(l, 1); l += shx(l, 4); l += shx(l, 8); l += shx(l, 16);
            sts64_p((lane & 29) == 0, sb + OFF_ML + (lane >> 1) * 64 + w * 8, F2U(mh), F2U(l));
        }
        __syncwarp();
        float oc[8][4];
#pragma unroll
        for (int i = 0; i < 8; i++) { oc[i][0] = 0.f; oc[i][1] = 0.f; oc[i][2] = 0.f; oc[i][3] = 0.f; }
        const uint32_t voff = sb + (w * 8 + (lane & 7)) * 256;
        const uint32_t vx = ((lane >> 3) ^ (lane & 6)) * 16;
#pragma unroll 1
        for (int c = 0; c < 8; c++) {
            uint32_t pb = lds32(pw + c * 32 + (g & 1) * 16 + tq * 4);
            pb = (g >> 1) == tq ? pb : 0u;
            mbar_wait(full + (8 + c) * 8);
            const uint32_t vb = voff + (c < 4 ? c + 8 : c - 4) * KV_BYTES;
#pragma unroll
            for (int j = 0; j < 4; j++) {
                const uint4 a = ldsm4t(vb + ((j * 64) ^ vx));
                mma8(oc[2 * j], a.x, a.y, pb);
                mma8(oc[2 * j + 1], a.z, a.w, pb);
            }
            mbar_arrive_p(lane == 0 && c < 5, empty + (8 + c) * 8);
        }
#pragma unroll
        for (int i = 0; i < 8; i += 2)
#pragma unroll
            for (int e = 0; e < 4; e++) oc[i][e] += shx(oc[i + 1][e], 1);
#pragma unroll
        for (int i = 0; i < 8; i += 4)
#pragma unroll
            for (int e = 0; e < 4; e++) {
                oc[i][e] += shx(oc[i + 2][e], 2);
                sts32_p(true, sb + OFF_RED + w * 1024 + (e & 1) * 512 + ((2 * i + (e >> 1)) ^ (2 * tq)) * 32 + g * 4, F2U(oc[i][e]));
            }
    }
    STAMP0(5);
    BAR_COMP(2);
    if (w < 8) {
        const uint32_t ml = sb + OFF_ML + (t >> 7) * 64;
        float mm[8], ll[8];
#pragma unroll
        for (int i = 0; i < 4; i++) { float4 a = lds128f(ml + i * 16); mm[2 * i] = a.x; ll[2 * i] = a.y; mm[2 * i + 1] = a.z; ll[2 * i + 1] = a.w; }
        float M = mm[0];
#pragma unroll
        for (int i = 1; i < 8; i++) M = fmaxf(M, mm[i]);
        float o = 0.f, L = 0.f;
#pragma unroll
        for (int i = 0; i < 8; i++) {
            float e = __expf(mm[i] - M);
            o = fmaf(e, lds32f(sb + OFF_RED + i * 1024 + t * 4), o);
            L = fmaf(e, ll[i], L);
        }
        const uint32_t lse = F2U(M + __logf(L));
        st_rlx_p(true, &sc->opart[h][w][s * 32 + lane], (F2U(__fdividef(o, L)) & ~3u) | ((lse >> lane & 1u) << 1) | tg);
    }
    STAMP0(6);
    st_rlx64(outp, ep, ep);
    ZERO44(ga)
#pragma unroll
    for (int j = 0; j < 4; j++) col_item(ga, 65536u + j * IT_BYTES, full + (16 + j) * 8, j, j);
    STAMP0(7);
    uint32_t isred = is_red && w < 8;
    const uint4* hslot = &sc->hx[(w & 7) * 2][tq * 2];
    uint4 hv[4];
#pragma unroll
    for (int i = 0; i < 4; i++) { hv[i] = make_uint4(ep, ep, ep, ep); ld_rlx128_p(hv[i], hslot + (i >> 1) * 8 + (i & 1), isred); }
    col_reduce(ga, sb + OFF_S, gg, uu);
    const uint32_t hp = geglu(gg, uu);

    float acc[4][4];
    ZERO44(acc)
    const uint32_t rwb = sb + (lrow * 9 + w) * 128, rwx = (lc ^ ((lrow + w) & 7)) * 16;
    auto row_item = [&](uint32_t off, uint32_t bar, uint32_t cp, int r0) {
        const uint32_t b0 = __shfl_sync(0xffffffffu, cp, r0 + tq * 2), b1 = __shfl_sync(0xffffffffu, cp, r0 + tq * 2 + 8);
        mbar_wait(bar);
#pragma unroll
        for (int i = 0; i < 4; i++) {
            const uint4 a = ldsm4t(rwb + ((i * 32) ^ rwx) + off);
            mma16(acc[i], a.x, a.y, a.z, a.w, b0, b1);
        }
    };
    row_item(65536u + 4 * IT_BYTES, full + 20 * 8, hp, 0);
    row_item(65536u + 5 * IT_BYTES, full + 21 * 8, hp, 16);
    STAMP0(9);
    const uint4* slot = &sc->outpart[is_red ? b : 0][t & 255];
    uint32_t l4 = lane & 4, l8 = lane & 8;
    uint32_t fin_st = sb + OFF_FIN + (tq * 2 + (lane >> 2 & 1) + (lane & 8)) * 80 + w * 4;
    if (isred) {
        for (uint32_t n = 0; stale(hv[0], tg) | stale(hv[1], tg) | stale(hv[2], tg) | stale(hv[3], tg); n++) {
#pragma unroll
            for (int i = 0; i < 4; i++) hv[i] = ld_rlx128(hslot + (i >> 1) * 8 + (i & 1));
            if (n > SPIN_LIMIT) __trap();
        }
        __syncwarp();
    }
    uint32_t hb[8];
#pragma unroll
    for (int i = 0; i < 4; i++) { hb[2 * i] = hi2(hv[i].x, hv[i].y); hb[2 * i + 1] = hi2(hv[i].z, hv[i].w); }
    mbar_wait(bar_o);
    const uint32_t op = lds32(sb + OFF_OEX + lane * 4);
    row_item(65536u + 6 * IT_BYTES, full + 22 * 8, op, 0);
    STAMP0(10);
    row_item(65536u + 7 * IT_BYTES, full + 23 * 8, op, 16);
    {
        const float v0 = sel4(acc[0][0], acc[1][0], acc[2][0], acc[3][0], tq), v1 = sel4(acc[0][2], acc[1][2], acc[2][2], acc[3][2], tq);
        st_rlx64(outp, (F2U(v0) & ~1u) | tg, (F2U(v1) & ~1u) | tg);
    }
    STAMP0(11);
    if (!is_red) return;
    if (w < 8) {
        uint4 fa = make_uint4(ep, ep, ep, ep), fb = fa;
        {
            float c0[4] = {0.f, 0.f, 0.f, 0.f}, c1[4] = {0.f, 0.f, 0.f, 0.f};
            const uint32_t cb = sb + (w * 64 + lrow) * 32 + (lc ^ (lrow >> 2 & 1)) * 16;
            mbar_wait(full + 24 * 8);
            STAMP0(22);
#pragma unroll
            for (int i = 0; i < 4; i++) {
                const uint4 a = ldsm4t(cb + i * 512);
                mma16((i & 1) ? c1 : c0, a.x, a.y, a.z, a.w, hb[2 * i], hb[2 * i + 1]);
            }
            sts32_p(tq < 2, sb + OFF_FIN + (g + tq * 8) * 80 + 32 + w * 4, F2U(selp(c0[2] + c1[2], c0[0] + c1[0], tq)));
        }
        if (P_AT) while ((int)(gtime32() - t_cta) < P_AT) {}
        for (uint32_t n = 0;; n++) {
            const uint32_t sa = stale(fa, tg), sb2 = stale(fb, tg);
            if (!(sa | sb2)) break;
            ld_rlx128_p(fa, slot, sa);
            ld_rlx128_p(fb, slot + 256, sb2);
            if (n > SPIN_LIMIT) __trap();
            if (PSLEEP) __nanosleep(PSLEEP);
        }
        __syncwarp();
        const float x0 = U2F(fa.x) + U2F(fb.x), x1 = U2F(fa.y) + U2F(fb.y), x2 = U2F(fa.z) + U2F(fb.z), x3 = U2F(fa.w) + U2F(fb.w);
        const float k0 = selp(x2, x0, l4) + shx(selp(x0, x2, l4), 4);
        const float k1 = selp(x3, x1, l4) + shx(selp(x1, x3, l4), 4);
        float k = selp(k1, k0, l8) + shx(selp(k0, k1, l8), 8);
        k += shx(k, 16);
        sts32_p(true, fin_st, F2U(k));
        STAMP0(23);
        asm volatile("bar.arrive 4, 288;" ::: "memory");
    } else {
        const uint32_t fa_ = sb + OFF_FIN + (lane & 15) * 80;
        uint16_t* op16 = out16 + b * 16 + (lane & 15);
        asm volatile("bar.sync 4, 288;" ::: "memory");
        const float4 p0 = lds128f(fa_), p1 = lds128f(fa_ + 16), p2 = lds128f(fa_ + 32), p3 = lds128f(fa_ + 48);
        const float r = ((((p0.x + p0.y) + (p0.z + p0.w)) + ((p1.x + p1.y) + (p1.z + p1.w))) +
                         (((p2.x + p2.y) + (p2.z + p2.w)) + ((p3.x + p3.y) + (p3.z + p3.w)))) + xres;
        if (lane < 16) *op16 = (uint16_t)pack2(r, 0.f);
        if (b == 0 && lane == 0) sc->epoch = ep + 1;
    }
}

typedef CUresult (*EncodeFn)(CUtensorMap*, CUtensorMapDataType, cuuint32_t, void*, const cuuint64_t*, const cuuint64_t*,
                             const cuuint32_t*, const cuuint32_t*, CUtensorMapInterleave, CUtensorMapSwizzle,
                             CUtensorMapL2promotion, CUtensorMapFloatOOBfill);

void make_map(EncodeFn fn, CUtensorMap* m, const void* p, int inner, int outer, int box_inner, int box_outer, CUtensorMapSwizzle sw) {
    cuuint64_t gd[2] = {(cuuint64_t)inner, (cuuint64_t)outer};
    cuuint64_t gs[1] = {(cuuint64_t)inner * 2};
    cuuint32_t bd[2] = {(cuuint32_t)box_inner, (cuuint32_t)box_outer};
    cuuint32_t es[2] = {1, 1};
    fn(m, CU_TENSOR_MAP_DATA_TYPE_BFLOAT16, 2, const_cast<void*>(p), gd, gs, bd, es, CU_TENSOR_MAP_INTERLEAVE_NONE,
       sw, CU_TENSOR_MAP_L2_PROMOTION_L2_128B, CU_TENSOR_MAP_FLOAT_OOB_FILL_NONE);
}

}

extern "C" void kernel_launch(void* const* d_in, const int* in_sizes, int n_in, void* d_out, int out_size) {
    (void)in_sizes; (void)n_in; (void)out_size;
    static EncodeFn enc_fn = nullptr;
    static void* scratch = nullptr;
    if (!enc_fn) {
        cudaDriverEntryPointQueryResult qr;
        void* fn = nullptr;
        cudaGetDriverEntryPoint("cuTensorMapEncodeTiled", &fn, cudaEnableDefault, &qr);
        enc_fn = (EncodeFn)fn;
        cudaGetSymbolAddress(&scratch, g_scratch);
        cudaFuncSetAttribute(fused_decode_kernel, cudaFuncAttributeMaxDynamicSharedMemorySize, SMEM_BYTES);
    }
    Maps maps;
    make_map(enc_fn, &maps.m[0], d_in[6], FF, D_MODEL, 32, 144, CU_TENSOR_MAP_SWIZZLE_64B);
    make_map(enc_fn, &maps.m[1], d_in[7], FF, D_MODEL, 32, 144, CU_TENSOR_MAP_SWIZZLE_64B);
    make_map(enc_fn, &maps.m[2], d_in[8], 64, FF * 9, 64, 144, CU_TENSOR_MAP_SWIZZLE_128B);
    make_map(enc_fn, &maps.m[3], d_in[4], 64, NQ * 9, 64, 144, CU_TENSOR_MAP_SWIZZLE_128B);
    make_map(enc_fn, &maps.m[4], d_in[8], D_MODEL, FF, 16, 256, CU_TENSOR_MAP_SWIZZLE_32B);
    make_map(enc_fn, &maps.m[5], d_in[3], NQ, D_MODEL, 32, 144, CU_TENSOR_MAP_SWIZZLE_64B);
    fused_decode_kernel<<<NCTA, NTHREADS, SMEM_BYTES>>>(
        (const uint32_t*)d_in[0], (const uint8_t*)d_in[1], (const uint8_t*)d_in[2],
        (uint16_t*)d_out, (Scratch*)scratch, maps);
}
```

```cpp
#include <cuda_runtime.h>
#include <cuda_bf16.h>
#include <cuda.h>
#include <stdint.h>

namespace {

constexpr int D_MODEL = 576;
constexpr int SK = 65536;
constexpr int WIN = 4096;
constexpr int NQ = 4096;
constexpr int FF = 4608;
constexpr int NMAIN = 128;
constexpr int NCTA = 132;
constexpr int NRED = 36;
constexpr int NTHREADS = 352;
#define PACE_W0 20000
#define PACE_NS 0.0408f
#define C_DELAY 400
constexpr int DEPTH = 6;
constexpr int QPOLL_FROM = 3, OPOLL_FROM = 18, HPOLL_FROM = 21;
constexpr int NCU = 8;
constexpr int CU0 = NMAIN - NCU;
constexpr int CLINES = (16 + NCU) / 8;
constexpr uint32_t KV_BYTES = 16384;
constexpr uint32_t IT_BYTES = 18432;
constexpr uint32_t WQ_OFF = 176128;
constexpr uint32_t MISC_OFF = 212992;
constexpr uint32_t OFF_FULL = MISC_OFF;
constexpr uint32_t OFF_EMPTY = MISC_OFF + 256;
constexpr uint32_t OFF_XN = MISC_OFF + 512;
constexpr uint32_t OFF_RED = OFF_XN + 1152;
constexpr uint32_t OFF_Q = OFF_RED + 9216;
constexpr uint32_t OFF_S = OFF_Q + 512;
constexpr uint32_t OFF_P = OFF_S + 4096;
constexpr uint32_t OFF_OEX = OFF_P + 2048;
constexpr uint32_t OFF_ML = OFF_OEX + 128;
constexpr uint32_t OFF_EP = OFF_ML + 128;
constexpr uint32_t OFF_HX = OFF_EP + 16;
constexpr uint32_t OFF_FIN = OFF_P;
constexpr uint32_t SMEM_BYTES = OFF_HX + (16 + NCU) * 64;
static_assert(SMEM_BYTES <= 232448, "smem");

constexpr uint32_t SPIN_LIMIT = 1u << 20;

struct Scratch {
    uint4 q[16][64];
    uint32_t opart[16][8][8 * 32];
    uint4 hx[16 + NCU][8];
    uint4 outpart[NRED][NMAIN * 4];
    uint32_t epoch[NCTA][32];
};
__device__ __align__(128) Scratch g_scratch;

struct Maps { CUtensorMap m[6]; };

__device__ __forceinline__ uint32_t gtime32() { uint32_t t; asm volatile("mov.u32 %0, %globaltimer_lo;" : "=r"(t)); return t; }
#define STAMP(i)
#define STAMP0(i)

__device__ __forceinline__ uint32_t s2u(const void* p) { return (uint32_t)__cvta_generic_to_shared(p); }
__device__ __forceinline__ void mbar_init(uint32_t a, uint32_t c) { asm volatile("mbarrier.init.shared::cta.b64 [%0], %1;" ::"r"(a), "r"(c) : "memory"); }
__device__ __forceinline__ void mbar_expect(uint32_t a, uint32_t b) { asm volatile("mbarrier.arrive.expect_tx.shared::cta.b64 _, [%0], %1;" ::"r"(a), "r"(b) : "memory"); }
__device__ __forceinline__ void mbar_wait(uint32_t a) {
    uint32_t ok, n = 0;
    do {
        asm volatile("{\n.reg .pred p;\nmbarrier.try_wait.parity.shared::cta.b64 p, [%1], 0;\nselp.u32 %0, 1, 0, p;\n}" : "=r"(ok) : "r"(a) : "memory");
        if (++n > SPIN_LIMIT) __trap();
    } while (!ok);
}
__device__ __forceinline__ bool mbar_test(uint32_t a) {
    uint32_t ok;
    asm volatile("{\n.reg .pred p;\nmbarrier.test_wait.parity.shared::cta.b64 p, [%1], 0;\nselp.u32 %0, 1, 0, p;\n}" : "=r"(ok) : "r"(a) : "memory");
    return ok;
}
__device__ __forceinline__ uint64_t policy_evict_first() { uint64_t p; asm("createpolicy.fractional.L2::evict_first.b64 %0, 1.0;" : "=l"(p)); return p; }
__device__ __forceinline__ uint64_t policy_evict_normal() { uint64_t p; asm("createpolicy.fractional.L2::evict_normal.b64 %0, 1.0;" : "=l"(p)); return p; }
__device__ __forceinline__ void bulk_ld(uint32_t dst, const void* src, uint32_t bytes, uint32_t bar, uint64_t pol) {
    asm volatile("cp.async.bulk.shared::cluster.global.mbarrier::complete_tx::bytes.L2::cache_hint [%0], [%1], %2, [%3], %4;"
                 ::"r"(dst), "l"(src), "r"(bytes), "r"(bar), "l"(pol) : "memory");
}
__device__ __forceinline__ void tma2d_ld(uint32_t dst, const CUtensorMap* m, int c0, int c1, uint32_t bar, uint64_t pol) {
    asm volatile("cp.async.bulk.tensor.2d.shared::cluster.global.mbarrier::complete_tx::bytes.L2::cache_hint [%0], [%1, {%3, %4}], [%2], %5;"
                 ::"r"(dst), "l"(m), "r"(bar), "r"(c0), "r"(c1), "l"(pol) : "memory");
}
__device__ __forceinline__ uint4 lds128(uint32_t a) { uint4 v; asm volatile("ld.shared.v4.u32 {%0,%1,%2,%3}, [%4];" : "=r"(v.x), "=r"(v.y), "=r"(v.z), "=r"(v.w) : "r"(a) : "memory"); return v; }
__device__ __forceinline__ float4 lds128f(uint32_t a) { float4 v; asm volatile("ld.shared.v4.f32 {%0,%1,%2,%3}, [%4];" : "=f"(v.x), "=f"(v.y), "=f"(v.z), "=f"(v.w) : "r"(a) : "memory"); return v; }
__device__ __forceinline__ uint32_t lds32(uint32_t a) { uint32_t v; asm volatile("ld.shared.u32 %0, [%1];" : "=r"(v) : "r"(a) : "memory"); return v; }
__device__ __forceinline__ float lds32f(uint32_t a) { float v; asm volatile("ld.shared.f32 %0, [%1];" : "=f"(v) : "r"(a) : "memory"); return v; }
__device__ __forceinline__ uint4 ldsm4t(uint32_t a) {
    uint4 v;
    asm volatile("ldmatrix.sync.aligned.m8n8.x4.trans.shared.b16 {%0,%1,%2,%3}, [%4];" : "=r"(v.x), "=r"(v.y), "=r"(v.z), "=r"(v.w) : "r"(a) : "memory");
    return v;
}
__device__ __forceinline__ void mma16(float (&c)[4], uint32_t a0, uint32_t a1, uint32_t a2, uint32_t a3, uint32_t b0, uint32_t b1) {
    asm volatile("mma.sync.aligned.m16n8k16.row.col.f32.bf16.bf16.f32 {%0,%1,%2,%3}, {%4,%5,%6,%7}, {%8,%9}, {%0,%1,%2,%3};"
                 : "+f"(c[0]), "+f"(c[1]), "+f"(c[2]), "+f"(c[3]) : "r"(a0), "r"(a1), "r"(a2), "r"(a3), "r"(b0), "r"(b1));
}
__device__ __forceinline__ void mma8(float (&c)[4], uint32_t a0, uint32_t a1, uint32_t b0) {
    asm volatile("mma.sync.aligned.m16n8k8.row.col.f32.bf16.bf16.f32 {%0,%1,%2,%3}, {%4,%5}, {%6}, {%0,%1,%2,%3};"
                 : "+f"(c[0]), "+f"(c[1]), "+f"(c[2]), "+f"(c[3]) : "r"(a0), "r"(a1), "r"(b0));
}
__device__ __forceinline__ uint32_t ldg_nc32(const void* p) { uint32_t v; asm volatile("ld.global.nc.u32 %0, [%1];" : "=r"(v) : "l"(p)); return v; }
__device__ __forceinline__ uint32_t ld_rlx(const uint32_t* p) { uint32_t v; asm volatile("ld.relaxed.gpu.global.u32 %0, [%1];" : "=r"(v) : "l"(p) : "memory"); return v; }
__device__ __forceinline__ uint4 ld_rlx128(const uint4* p) { uint4 v; asm volatile("ld.relaxed.gpu.global.v4.u32 {%0,%1,%2,%3}, [%4];" : "=r"(v.x), "=r"(v.y), "=r"(v.z), "=r"(v.w) : "l"(p) : "memory"); return v; }
__device__ __forceinline__ void ld_rlx128_p(uint4& v, const uint4* p, uint32_t en) {
    asm volatile("{\n.reg .pred p;\nsetp.ne.u32 p, %5, 0;\n@p ld.relaxed.gpu.global.v4.u32 {%0,%1,%2,%3}, [%4];\n}"
                 : "+r"(v.x), "+r"(v.y), "+r"(v.z), "+r"(v.w) : "l"(p), "r"(en) : "memory");
}
__device__ __forceinline__ void st_rlx64(uint32_t* p, uint32_t a, uint32_t b) { asm volatile("st.relaxed.gpu.global.v2.u32 [%0], {%1,%2};" ::"l"(p), "r"(a), "r"(b) : "memory"); }

__device__ __forceinline__ float bf_lo(uint32_t u) { return __uint_as_float(u << 16); }
__device__ __forceinline__ float bf_hi(uint32_t u) { return __uint_as_float(u & 0xffff0000u); }
__device__ __forceinline__ uint32_t pack2(float lo, float hi) { uint32_t r; asm("cvt.rn.bf16x2.f32 %0, %1, %2;" : "=r"(r) : "f"(hi), "f"(lo)); return r; }
__device__ __forceinline__ float bfr(float v) { return __uint_as_float(pack2(0.f, v)); }
__device__ __forceinline__ float shx(float v, int o) { return __shfl_xor_sync(0xffffffffu, v, o); }
__device__ __forceinline__ uint32_t hi2(uint32_t a, uint32_t b) { return __byte_perm(a, b, 0x7632); }

__device__ __forceinline__ void sts32_p(bool en, uint32_t a, uint32_t v) {
    asm volatile("{\n.reg .pred p;\nsetp.ne.u32 p, %2, 0;\n@p st.shared.u32 [%0], %1;\n}" ::"r"(a), "r"(v), "r"((uint32_t)en) : "memory");
}
__device__ __forceinline__ void sts64_p(bool en, uint32_t a, uint32_t x, uint32_t y) {
    asm volatile("{\n.reg .pred p;\nsetp.ne.u32 p, %3, 0;\n@p st.shared.v2.u32 [%0], {%1,%2};\n}" ::"r"(a), "r"(x), "r"(y), "r"((uint32_t)en) : "memory");
}
__device__ __forceinline__ void st_rlx_p(bool en, uint32_t* p, uint32_t v) {
    asm volatile("{\n.reg .pred p;\nsetp.ne.u32 p, %2, 0;\n@p st.relaxed.gpu.global.u32 [%0], %1;\n}" ::"l"(p), "r"(v), "r"((uint32_t)en) : "memory");
}
__device__ __forceinline__ void mbar_arrive_p(bool en, uint32_t a) {
    asm volatile("{\n.reg .pred p;\nsetp.ne.u32 p, %1, 0;\n@p mbarrier.arrive.shared::cta.b64 _, [%0];\n}" ::"r"(a), "r"((uint32_t)en) : "memory");
}
__device__ __forceinline__ uint32_t lop_ne(uint32_t a, uint32_t b, uint32_t c) { uint32_t r; asm("lop3.b32 %0, %1, %2, %3, 0x7E;" : "=r"(r) : "r"(a), "r"(b), "r"(c)); return r; }
__device__ __forceinline__ uint32_t stale(const uint4& v, uint32_t tg) { return (lop_ne(v.x, v.y, tg) | lop_ne(v.z, v.w, tg)) & 1u; }
__device__ __forceinline__ float selp(float a, float b, uint32_t c) { float r; asm("{\n.reg .pred p;\nsetp.ne.u32 p, %3, 0;\nselp.f32 %0, %1, %2, p;\n}" : "=f"(r) : "f"(a), "f"(b), "r"(c)); return r; }
__device__ __forceinline__ float sel4(float a0, float a1, float a2, float a3, uint32_t i) { return selp(selp(a3, a2, i & 1), selp(a1, a0, i & 1), i & 2); }
#define F2U __float_as_uint
#define U2F __uint_as_float
#define BAR_COMP(id) asm volatile("bar.sync " #id ", 288;" ::: "memory")
#define ZERO44(A) _Pragma("unroll") for (int i_ = 0; i_ < 4; i_++) { A[i_][0] = 0.f; A[i_][1] = 0.f; A[i_][2] = 0.f; A[i_][3] = 0.f; }

__global__ void __launch_bounds__(NTHREADS, 1)
fused_decode_kernel(const uint32_t* __restrict__ x32, const uint8_t* __restrict__ kc, const uint8_t* __restrict__ vc,
                    uint16_t* __restrict__ out16, Scratch* sc, const __grid_constant__ Maps maps) {
    extern __shared__ __align__(1024) uint8_t smem[];
    const uint32_t sb = s2u(smem);
    const int lane = threadIdx.x & 31, wid = threadIdx.x >> 5;
    const int b = blockIdx.x, h = b >> 3, s = b & 7;
    const bool is_main = b < NMAIN, is_red = b < NRED;
    const uint32_t full = sb + OFF_FULL, empty = sb + OFF_EMPTY;
    const uint32_t bar_q = sb + OFF_FULL + 27 * 8, bar_o = bar_q + 8, bar_h = bar_q + 16;
    const size_t kvoff = ((size_t)h * SK + (SK - WIN) + s * 64) * 256;

    if (threadIdx.x == 0) {
        mbar_init(full, 1);
        if (is_main) {
            mbar_expect(full, KV_BYTES);
            bulk_ld(sb, kc + kvoff, KV_BYTES, full, policy_evict_first());
        }
    }
    if (threadIdx.x == 32 && is_main) {
#pragma unroll
        for (int i = 0; i < 2; i++) {
            mbar_init(full + (25 + i) * 8, 1);
            mbar_expect(full + (25 + i) * 8, IT_BYTES);
            tma2d_ld(sb + WQ_OFF + i * IT_BYTES, &maps.m[5], b * 32, i * 288, full + (25 + i) * 8, policy_evict_normal());
            tma2d_ld(sb + WQ_OFF + i * IT_BYTES + 9216, &maps.m[5], b * 32, i * 288 + 144, full + (25 + i) * 8, policy_evict_normal());
        }
        STAMP(18);
    }
    if (wid == 0) {
        const uint32_t t_start = gtime32() - 150;
        if (lane == 0) {
#pragma unroll
            for (int i = 1; i < 25; i++) mbar_init(full + i * 8, 1);
            mbar_init(bar_q, 32);
            mbar_init(bar_o, 32);
            mbar_init(bar_h, 32);
            const uint32_t cnt = is_main ? 8 : 9;
#pragma unroll
            for (int i = 0; i < 13; i++) mbar_init(empty + i * 8, cnt);
            mbar_init(empty + 13 * 8, 9);
        }
        __syncwarp();
        asm volatile("bar.arrive 15, %0;" ::"n"(NTHREADS) : "memory");
        const int i = lane;
        const int j = is_main ? i - 16 : i & 3;
        const int unit = is_main ? b : NMAIN + (b - NMAIN) * 4 + (i >> 2);
        const uint32_t off = !is_main ? (i % 11) * IT_BYTES : i < 12 ? i * KV_BYTES : i < 16 ? (i - 12) * KV_BYTES : i < 24 ? 65536u + (i - 16) * IT_BYTES : 0u;
        const int dep = is_main ? (i < 10 ? -1 : i < 12 ? 13 : i < 16 ? i - 12 : i < 24 ? min(i - 11, 11) : 12) : i - 11;
        const bool skipd = is_main && b >= CU0;
        const int prev = i == 24 ? 21 : i - DEPTH;
        const uint32_t esc = full + (skipd && i == 22 ? 19 : max(i - 1, 0)) * 8;
        const uint8_t* src = (i < 8 ? kc : vc) + kvoff + (i & 7) * (8 * KV_BYTES);
        const CUtensorMap* mp = &maps.m[j < 4 ? 0 : min(j >> 1, 4)];
        const int c0 = j < 4 ? unit * 32 : j < 8 ? 0 : b * 16;
        const int c1 = j < 4 ? j * 144 : j < 8 ? unit * 288 + (j & 1) * 144 : CU0 * 32;
        const uint32_t dst = sb + off, bar = full + i * 8;
        const uint64_t pol = (j < 0 || (j >= 4 && j < 8)) ? policy_evict_first() : policy_evict_normal();
        const int i0 = is_main ? 1 : 0, i1 = is_red ? 25 : is_main ? 24 : 16;
        const int cum = is_main ? 2 * IT_BYTES + (i < 16 ? i * KV_BYTES : 16 * KV_BYTES + (i - 16) * IT_BYTES) : i * IT_BYTES;
        int t_rel = (int)((float)(cum - PACE_W0 + b * 128) * PACE_NS);
        if (i >= i0 && i < i1) mbar_expect(bar, j < 0 ? KV_BYTES : j == 8 ? CLINES * 8192 : IT_BYTES);
        if (lane >= 27) asm volatile("prefetch.tensormap [%0];" ::"l"(&maps.m[lane - 27]) : "memory");
#pragma unroll 1
        for (int k = i0; k < i1; k++) {
            if (lane == k && !(skipd && (k == 20 || k == 21))) {
                if (prev >= 0) mbar_wait(full + prev * 8);
                if (dep >= 0) mbar_wait(empty + dep * 8);
                if (k == 24) t_rel = (int)(gtime32() - t_start) + C_DELAY;
                while ((int)(gtime32() - t_start) < t_rel && !mbar_test(esc)) {}
                if (j < 0) {
                    bulk_ld(dst, src, KV_BYTES, bar, pol);
                } else {
                    tma2d_ld(dst, mp, c0, c1, bar, pol);
                    if (j < 4) tma2d_ld(dst + 9216, mp + 1, c0, c1, bar, pol);
                    if (j == 8) {
#pragma unroll
                        for (int q = 1; q < CLINES; q++) tma2d_ld(dst + q * 8192, mp, c0, c1 + q * 256, bar, pol);
                    }
                }
            }
            __syncwarp();
        }
        return;
    }
    if (wid == 1) {
        asm volatile("bar.sync 15, %0;" ::"n"(NTHREADS) : "memory");
        if (!is_main) return;
        const uint32_t tg = ~lds32(sb + OFF_EP) & 1u;
        uint32_t n = 0;
        {
            mbar_wait(full + QPOLL_FROM * 8);
            uint4 a, c;
            for (;;) {
                a = ld_rlx128(&sc->q[h][lane * 2]);
                c = ld_rlx128(&sc->q[h][lane * 2 + 1]);
                if (!__any_sync(0xffffffffu, stale(a, tg) | stale(c, tg))) break;
                if (++n > SPIN_LIMIT) __trap();
                __nanosleep(100);
            }
            asm volatile("st.shared.v4.u32 [%0], {%1,%2,%3,%4};" ::"r"(sb + OFF_Q + lane * 16), "r"(hi2(a.x, a.y)), "r"(hi2(a.z, a.w)),
                         "r"(hi2(c.x, c.y)), "r"(hi2(c.z, c.w)) : "memory");
            mbar_arrive_p(true, bar_q);
        }
        {
            const uint32_t* slot = &sc->opart[h][s][lane];
            mbar_wait(full + OPOLL_FROM * 8);
            uint32_t ov[8];
            for (;;) {
                uint32_t bad = 0;
#pragma unroll
                for (int i = 0; i < 8; i++) { ov[i] = ld_rlx(slot + i * 32); bad |= ov[i] ^ tg; }
                if (__all_sync(0xffffffffu, !(bad & 1u))) break;
                if (++n > SPIN_LIMIT) __trap();
                __nanosleep(100);
            }
            float lse[8], M = -INFINITY;
#pragma unroll
            for (int i = 0; i < 8; i++) { lse[i] = U2F(__ballot_sync(0xffffffffu, ov[i] & 2u)); M = fmaxf(M, lse[i]); }
            float o = 0.f, L = 0.f;
#pragma unroll
            for (int i = 0; i < 8; i++) {
                const float e = __expf(lse[i] - M);
                o = fmaf(e, U2F(ov[i]), o);
                L += e;
            }
            o = __fdividef(o, L);
            sts32_p(true, sb + OFF_OEX + lane * 4, pack2(o, __shfl_down_sync(0xffffffffu, o, 1)));
            mbar_arrive_p(true, bar_o);
        }
        if (is_red) {
            mbar_wait(full + HPOLL_FROM * 8);
            uint4 hv[2 * CLINES];
            for (;;) {
                uint32_t bad = 0;
#pragma unroll
                for (int i = 0; i < 2 * CLINES; i++) { hv[i] = ld_rlx128(&sc->hx[0][0] + i * 32 + lane); bad |= stale(hv[i], tg); }
                if (!__any_sync(0xffffffffu, bad)) break;
                if (++n > SPIN_LIMIT) __trap();
                __nanosleep(100);
            }
#pragma unroll
            for (int i = 0; i < 2 * CLINES; i++) sts64_p(true, sb + OFF_HX + i * 256 + lane * 8, hi2(hv[i].x, hv[i].y), hi2(hv[i].z, hv[i].w));
            mbar_arrive_p(true, bar_h);
        }
        return;
    }

    const int w = wid - 2, t = threadIdx.x - 64;
    const int g = lane >> 2, tq = lane & 3;
    float xres;
    {
        const uint32_t xr = ldg_nc32(x32 + (is_red ? b : 0) * 8 + (lane >> 1 & 7));
        xres = (lane & 1) ? bf_hi(xr) : bf_lo(xr);
        uint32_t xa[9];
#pragma unroll
        for (int i = 0; i < 9; i++) xa[i] = ldg_nc32(x32 + i * 32 + lane);
        const uint32_t xmine = ldg_nc32(x32 + t);
        if (t == 0) {
            const uint32_t e = sc->epoch[b][0];
            sc->epoch[b][0] = e + 1;
            sts32_p(true, sb + OFF_EP, e);
        }
        float sum = 0.f;
#pragma unroll
        for (int i = 0; i < 9; i++) sum += bf_lo(xa[i]) + bf_hi(xa[i]);
#pragma unroll
        for (int o = 16; o; o >>= 1) sum += shx(sum, o);
        const float mean = sum * (1.0f / D_MODEL);
        float sq = 0.f;
#pragma unroll
        for (int i = 0; i < 9; i++) { float a = bf_lo(xa[i]) - mean, c = bf_hi(xa[i]) - mean; sq = fmaf(a, a, fmaf(c, c, sq)); }
#pragma unroll
        for (int o = 16; o; o >>= 1) sq += shx(sq, o);
        const float m_bf = bfr(mean);
        const float sd = bfr(sqrtf(bfr(bfr(sq * (1.0f / D_MODEL)) + 1e-5f)));
        sts32_p(true, sb + OFF_XN + t * 4, pack2(bfr(bf_lo(xmine) - m_bf) / sd, bfr(bf_hi(xmine) - m_bf) / sd));
        STAMP0(1);
        asm volatile("bar.sync 15, %0;" ::"n"(NTHREADS) : "memory");
    }

    const uint32_t ep = lds32(sb + OFF_EP), tg = ~ep & 1u;
    const int lrow = (lane >> 4) * 8 + (lane & 7), lc = lane >> 3 & 1;
    const uint32_t gu0 = sb + (w * 16 + lrow) * 64 + (lc ^ (lrow >> 1 & 3)) * 16;
    const uint32_t xaddr = sb + OFF_XN + w * 32 + tq * 4;

    auto col_item = [&](float (&ga)[4][4], uint32_t off, uint32_t bar, int ra, int rb) {
        const uint32_t xA = xaddr + ra * 288, xB = xaddr + rb * 288;
        const uint32_t b0 = lds32(xA), b1 = lds32(xA + 16), b2 = lds32(xB), b3 = lds32(xB + 16);
        mbar_wait(bar);
#pragma unroll
        for (int i = 0; i < 4; i++) {
            const uint4 a = ldsm4t((gu0 ^ ((i & 1) * 32)) + off + (i >> 1) * 9216);
            mma16(ga[i], a.x, a.y, a.z, a.w, i < 2 ? b0 : b2, i < 2 ? b1 : b3);
        }
    };
    auto col_reduce = [&](float (&ga)[4][4], uint32_t red, float& gg, float& uu) {
        const float v0 = sel4(ga[0][0], ga[1][0], ga[2][0], ga[3][0], tq), v1 = sel4(ga[0][2], ga[1][2], ga[2][2], ga[3][2], tq);
        sts32_p(true, red + w * 256 + tq * 64 + g * 4, F2U(v0));
        sts32_p(true, red + w * 256 + tq * 64 + g * 4 + 32, F2U(v1));
        BAR_COMP(3);
        gg = 0.f; uu = 0.f;
#pragma unroll
        for (int k = 0; k < 9; k++) { gg += lds32f(red + k * 256 + lane * 4); uu += lds32f(red + k * 256 + 128 + lane * 4); }
    };
    auto geglu = [&](float gg, float uu) {
        gg = bfr(gg); uu = bfr(uu);
        const float inner = 0.7978845608028654f * (gg + 0.044715f * gg * gg * gg);
        const float hv = bfr(__fdividef(gg, 1.0f + __expf(-2.0f * inner))) * uu;
        return pack2(hv, __shfl_down_sync(0xffffffffu, hv, 1));
    };

    if (!is_main) {
        int it = 0;
        uint32_t off = 0;
#pragma unroll 1
        for (int u = 0; u < 4; u++) {
            float ga[4][4], gg, uu;
            ZERO44(ga)
#pragma unroll 1
            for (int j = 0; j < 4; j++) {
                col_item(ga, off, full + it * 8, j, j);
                mbar_arrive_p(lane == 0 && it < 5, empty + it * 8);
                it++; off = off == 10 * IT_BYTES ? 0u : off + IT_BYTES;
            }
            col_reduce(ga, sb + OFF_RED + (u & 1) * 2304, gg, uu);
            const uint32_t hp = geglu(gg, uu);
            st_rlx_p(w == 8, reinterpret_cast<uint32_t*>(&sc->hx[NCU + (b - NMAIN) * 4 + u][0]) + (lane >> 1 & 3) * 8 + (lane >> 3) * 2 + (lane & 1), hp << 16 | tg);
        }
        return;
    }

    uint32_t* outp = reinterpret_cast<uint32_t*>(&sc->outpart[w * 4 + tq][b * 4]) + g * 2;
    st_rlx64(outp, ep, ep);
    st_rlx_p(w < 8, &sc->opart[h][w & 7][s * 32 + lane], ep);
    st_rlx_p(w == 8, reinterpret_cast<uint32_t*>(&sc->q[h][s * 8]) + lane, ep);
    st_rlx_p(w == 8 && b >= CU0, reinterpret_cast<uint32_t*>(&sc->hx[max(b - CU0, 0)][0]) + lane, ep);
    float ga[4][4], gg, uu;
    ZERO44(ga)
    col_item(ga, WQ_OFF, full + 25 * 8, 0, 1);
    col_item(ga, WQ_OFF + IT_BYTES, full + 26 * 8, 2, 3);
    mbar_arrive_p(lane == 0, empty + 13 * 8);
    STAMP0(19);
    col_reduce(ga, sb + OFF_RED, gg, uu);
    st_rlx_p(w == 8, reinterpret_cast<uint32_t*>(&sc->q[h][s * 8]) + lane, pack2(0.f, gg + uu) | tg);
    STAMP0(2);
    if (w < 8) {
        mbar_wait(bar_q);
        STAMP0(3);
        uint4 qf[4];
#pragma unroll
        for (int j = 0; j < 4; j++) qf[j] = lds128(sb + OFF_Q + (g & 1) * 256 + ((j ^ (g >> 1 & 1)) * 4 + tq) * 16);
        const uint32_t koff = sb + (w * 8 + g) * 256 + tq * 16;
        const uint32_t kx = (g & 1) * 64;
        const uint32_t sw = sb + OFF_S + w * 512, pw = sb + OFF_P + w * 256;
        float m = -INFINITY;
#pragma unroll 2
        for (int c = 0; c < 8; c++) {
            mbar_wait(full + c * 8);
            uint4 kv[4];
#pragma unroll
            for (int j = 0; j < 4; j++) kv[j] = lds128(koff + c * KV_BYTES + ((j * 64) ^ kx));
            float c0[4] = {0.f, 0.f, 0.f, 0.f}, c1[4] = {0.f, 0.f, 0.f, 0.f};
#pragma unroll
            for (int j = 0; j < 4; j++) {
                mma16(c0, qf[j].x, qf[j].x, qf[j].y, qf[j].y, kv[j].x, kv[j].y);
                mma16(c1, qf[j].z, qf[j].z, qf[j].w, qf[j].w, kv[j].z, kv[j].w);
            }
            mbar_arrive_p(lane == 0, empty + c * 8);
            const float raw = (g & 2) ? c0[1] + c1[1] : c0[0] + c1[0];
            const float scv = bfr(bfr(raw) * 0.08838834764831845f);
            m = fmaxf(m, scv);
            sts32_p(g < 4, sw + c * 64 + (g & 1) * 32 + tq * 8 + (g & 2) * 2, F2U(scv));
        }
        STAMP0(4);
        m = fmaxf(m, shx(m, 1)); m = fmaxf(m, shx(m, 2)); m = fmaxf(m, shx(m, 8));
        __syncwarp();
        {
            const float mh = __shfl_sync(0xffffffffu, m, (lane & 2) * 2);
            const float4 sv = lds128f(sw + lane * 16);
            const uint32_t p01 = pack2(__expf(sv.x - mh), __expf(sv.y - mh)), p23 = pack2(__expf(sv.z - mh), __expf(sv.w - mh));
            sts64_p(true, pw + lane * 8, p01, p23);
            float l = (bf_lo(p01) + bf_hi(p01)) + (bf_lo(p23) + bf_hi(p23));
            l += shx(l, 1); l += shx(l, 4); l += shx(l, 8); l += shx(l, 16);
            sts64_p((lane & 29) == 0, sb + OFF_ML + (lane >> 1) * 64 + w * 8, F2U(mh), F2U(l));
        }
        __syncwarp();
        float oc[8][4];
#pragma unroll
        for (int i = 0; i < 8; i++) { oc[i][0] = 0.f; oc[i][1] = 0.f; oc[i][2] = 0.f; oc[i][3] = 0.f; }
        const uint32_t voff = sb + (w * 8 + (lane & 7)) * 256;
        const uint32_t vx = ((lane >> 3) ^ (lane & 6)) * 16;
#pragma unroll 1
        for (int c = 0; c < 8; c++) {
            uint32_t pb = lds32(pw + c * 32 + (g & 1) * 16 + tq * 4);
            pb = (g >> 1) == tq ? pb : 0u;
            mbar_wait(full + (8 + c) * 8);
            const uint32_t vb = voff + (c < 4 ? c + 8 : c - 4) * KV_BYTES;
#pragma unroll
            for (int j = 0; j < 4; j++) {
                const uint4 a = ldsm4t(vb + ((j * 64) ^ vx));
                mma8(oc[2 * j], a.x, a.y, pb);
                mma8(oc[2 * j + 1], a.z, a.w, pb);
            }
            mbar_arrive_p(lane == 0 && (c < 4 || c == 5), empty + min(8 + c, 12) * 8);
        }
#pragma unroll
        for (int i = 0; i < 8; i += 2)
#pragma unroll
            for (int e = 0; e < 4; e++) oc[i][e] += shx(oc[i + 1][e], 1);
#pragma unroll
        for (int i = 0; i < 8; i += 4)
#pragma unroll
            for (int e = 0; e < 4; e++) {
                oc[i][e] += shx(oc[i + 2][e], 2);
                sts32_p(true, sb + OFF_RED + w * 1024 + (e & 1) * 512 + ((2 * i + (e >> 1)) ^ (2 * tq)) * 32 + g * 4, F2U(oc[i][e]));
            }
    }
    STAMP0(5);
    BAR_COMP(2);
    if (w < 8) {
        const uint32_t ml = sb + OFF_ML + (t >> 7) * 64;
        float mm[8], ll[8];
#pragma unroll
        for (int i = 0; i < 4; i++) { float4 a = lds128f(ml + i * 16); mm[2 * i] = a.x; ll[2 * i] = a.y; mm[2 * i + 1] = a.z; ll[2 * i + 1] = a.w; }
        float M = mm[0];
#pragma unroll
        for (int i = 1; i < 8; i++) M = fmaxf(M, mm[i]);
        float o = 0.f, L = 0.f;
#pragma unroll
        for (int i = 0; i < 8; i++) {
            float e = __expf(mm[i] - M);
            o = fmaf(e, lds32f(sb + OFF_RED + i * 1024 + t * 4), o);
            L = fmaf(e, ll[i], L);
        }
        const uint32_t lse = F2U(M + __logf(L));
        st_rlx_p(true, &sc->opart[h][w][s * 32 + lane], (F2U(__fdividef(o, L)) & ~3u) | ((lse >> lane & 1u) << 1) | tg);
    }
    STAMP0(6);
    ZERO44(ga)
#pragma unroll
    for (int j = 0; j < 4; j++) col_item(ga, 65536u + j * IT_BYTES, full + (16 + j) * 8, j, j);
    STAMP0(7);
    col_reduce(ga, sb + OFF_S, gg, uu);
    const uint32_t hp = geglu(gg, uu);

    float acc[4][4];
    ZERO44(acc)
    const uint32_t rwb = sb + (lrow * 9 + w) * 128, rwx = (lc ^ ((lrow + w) & 7)) * 16;
    auto row_item = [&](uint32_t off, uint32_t bar, uint32_t cp, int r0) {
        const uint32_t b0 = __shfl_sync(0xffffffffu, cp, r0 + tq * 2), b1 = __shfl_sync(0xffffffffu, cp, r0 + tq * 2 + 8);
        mbar_wait(bar);
#pragma unroll
        for (int i = 0; i < 4; i++) {
            const uint4 a = ldsm4t(rwb + ((i * 32) ^ rwx) + off);
            mma16(acc[i], a.x, a.y, a.z, a.w, b0, b1);
        }
    };
    if (b < CU0) {
        row_item(65536u + 4 * IT_BYTES, full + 20 * 8, hp, 0);
        row_item(65536u + 5 * IT_BYTES, full + 21 * 8, hp, 16);
    } else {
        st_rlx_p(w == 8, reinterpret_cast<uint32_t*>(&sc->hx[b - CU0][0]) + (lane >> 1 & 3) * 8 + (lane >> 3) * 2 + (lane & 1), hp << 16 | tg);
    }
    STAMP0(9);
    const uint4* slot = &sc->outpart[is_red ? b : 0][t & 255];
    uint32_t l4 = lane & 4, l8 = lane & 8;
    uint32_t fin_st = sb + OFF_FIN + (tq * 2 + (lane >> 2 & 1) + (lane & 8)) * 80 + w * 4;
    mbar_wait(bar_o);
    const uint32_t op = lds32(sb + OFF_OEX + lane * 4);
    row_item(65536u + 6 * IT_BYTES, full + 22 * 8, op, 0);
    STAMP0(10);
    row_item(65536u + 7 * IT_BYTES, full + 23 * 8, op, 16);
    {
        const float v0 = sel4(acc[0][0], acc[1][0], acc[2][0], acc[3][0], tq), v1 = sel4(acc[0][2], acc[1][2], acc[2][2], acc[3][2], tq);
        st_rlx64(outp, (F2U(v0) & ~1u) | tg, (F2U(v1) & ~1u) | tg);
    }
    STAMP0(11);
    if (!is_red) return;
    if (w < 8) {
        uint4 fa = make_uint4(ep, ep, ep, ep), fb = fa;
        {
            float c0[4] = {0.f, 0.f, 0.f, 0.f}, c1[4] = {0.f, 0.f, 0.f, 0.f};
            const uint32_t cb = sb + (w * (32 * CLINES) + lrow) * 32 + (lc ^ (lrow >> 2 & 1)) * 16;
            mbar_wait(bar_h);
            uint4 hb[CLINES];
#pragma unroll
            for (int i = 0; i < CLINES; i++) hb[i] = lds128(sb + OFF_HX + (w * CLINES + i) * 64 + tq * 16);
            mbar_wait(full + 24 * 8);
            STAMP0(22);
#pragma unroll
            for (int i = 0; i < CLINES; i++) {
                const uint4 a = ldsm4t(cb + i * 1024), e = ldsm4t(cb + i * 1024 + 512);
                mma16(c0, a.x, a.y, a.z, a.w, hb[i].x, hb[i].y);
                mma16(c1, e.x, e.y, e.z, e.w, hb[i].z, hb[i].w);
            }
            sts32_p(tq < 2, sb + OFF_FIN + (g + tq * 8) * 80 + 32 + w * 4, F2U(selp(c0[2] + c1[2], c0[0] + c1[0], tq)));
        }
        for (uint32_t n = 0;; n++) {
            const uint32_t sa = stale(fa, tg), sb2 = stale(fb, tg);
            if (!(sa | sb2)) break;
            ld_rlx128_p(fa, slot, sa);
            ld_rlx128_p(fb, slot + 256, sb2);
            if (n > SPIN_LIMIT) __trap();
        }
        __syncwarp();
        const float x0 = U2F(fa.x) + U2F(fb.x), x1 = U2F(fa.y) + U2F(fb.y), x2 = U2F(fa.z) + U2F(fb.z), x3 = U2F(fa.w) + U2F(fb.w);
        const float k0 = selp(x2, x0, l4) + shx(selp(x0, x2, l4), 4);
        const float k1 = selp(x3, x1, l4) + shx(selp(x1, x3, l4), 4);
        float k = selp(k1, k0, l8) + shx(selp(k0, k1, l8), 8);
        k += shx(k, 16);
        sts32_p(true, fin_st, F2U(k));
        STAMP0(23);
        asm volatile("bar.arrive 4, 288;" ::: "memory");
    } else {
        const uint32_t fa_ = sb + OFF_FIN + (lane & 15) * 80;
        uint16_t* op16 = out16 + b * 16 + (lane & 15);
        asm volatile("bar.sync 4, 288;" ::: "memory");
        const float4 p0 = lds128f(fa_), p1 = lds128f(fa_ + 16), p2 = lds128f(fa_ + 32), p3 = lds128f(fa_ + 48);
        const float r = ((((p0.x + p0.y) + (p0.z + p0.w)) + ((p1.x + p1.y) + (p1.z + p1.w))) +
                         (((p2.x + p2.y) + (p2.z + p2.w)) + ((p3.x + p3.y) + (p3.z + p3.w)))) + xres;
        if (lane < 16) *op16 = (uint16_t)pack2(r, 0.f);
    }
}

__device__ float g_fb[NQ + NQ + FF];
__device__ __forceinline__ float ldbf(const uint16_t* p, size_t i) { return __uint_as_float((uint32_t)p[i] << 16); }
__device__ float fb_block_reduce(float v, bool is_max, float* sh) {
    for (int o = 16; o; o >>= 1) { const float u = shx(v, o); v = is_max ? fmaxf(v, u) : v + u; }
    __syncthreads();
    if ((threadIdx.x & 31) == 0) sh[threadIdx.x >> 5] = v;
    __syncthreads();
    v = sh[0];
    for (int i = 1; i < (int)blockDim.x / 32; i++) v = is_max ? fmaxf(v, sh[i]) : v + sh[i];
    return v;
}
__global__ void fb_proj(const uint16_t* x, const uint16_t* wq, const uint16_t* wg, const uint16_t* wu) {
    __shared__ float xn[D_MODEL], sh[8];
    float a = 0.f;
    for (int i = threadIdx.x; i < D_MODEL; i += 128) a += ldbf(x, i);
    const float mean = fb_block_reduce(a, false, sh) / D_MODEL;
    a = 0.f;
    for (int i = threadIdx.x; i < D_MODEL; i += 128) { const float d = ldbf(x, i) - mean; a += d * d; }
    const float sd = bfr(sqrtf(bfr(bfr(fb_block_reduce(a, false, sh) / D_MODEL) + 1e-5f)));
    for (int i = threadIdx.x; i < D_MODEL; i += 128) xn[i] = bfr(bfr(ldbf(x, i) - bfr(mean)) / sd);
    __syncthreads();
    const int c = blockIdx.x * 128 + threadIdx.x;
    if (c < NQ) {
        float q = 0.f;
        for (int r = 0; r < D_MODEL; r++) q = fmaf(xn[r], ldbf(wq, (size_t)r * NQ + c), q);
        g_fb[c] = bfr(q);
    } else {
        float g = 0.f, u = 0.f;
        for (int r = 0; r < D_MODEL; r++) { g = fmaf(xn[r], ldbf(wg, (size_t)r * FF + c - NQ), g); u = fmaf(xn[r], ldbf(wu, (size_t)r * FF + c - NQ), u); }
        g = bfr(g); u = bfr(u);
        g_fb[NQ + c] = bfr(bfr(0.5f * g * (1.f + tanhf(0.7978845608028654f * (g + 0.044715f * g * g * g)))) * u);
    }
}
__global__ void fb_attn(const uint16_t* kc, const uint16_t* vc) {
    __shared__ float p[WIN], sh[8];
    const size_t base = ((size_t)(blockIdx.x >> 1) * SK + (SK - WIN)) * 128;
    float m = -INFINITY;
    for (int k = threadIdx.x; k < WIN; k += 128) {
        float a = 0.f;
        for (int d = 0; d < 128; d++) a = fmaf(g_fb[blockIdx.x * 128 + d], ldbf(kc, base + (size_t)k * 128 + d), a);
        p[k] = bfr(bfr(a) * 0.08838834764831845f);
        m = fmaxf(m, p[k]);
    }
    m = fb_block_reduce(m, true, sh);
    float l = 0.f;
    for (int k = threadIdx.x; k < WIN; k += 128) { p[k] = __expf(p[k] - m); l += p[k]; }
    l = fb_block_reduce(l, false, sh);
    float o = 0.f;
    for (int k = 0; k < WIN; k++) o = fmaf(p[k], ldbf(vc, base + (size_t)k * 128 + threadIdx.x), o);
    g_fb[NQ + blockIdx.x * 128 + threadIdx.x] = bfr(o / l);
}
__global__ void fb_out(const uint16_t* x, const uint16_t* wo, const uint16_t* wd, uint16_t* out) {
    __shared__ float sh[8];
    const int c = blockIdx.x;
    float a = 0.f;
    for (int r = threadIdx.x; r < NQ; r += 128) a = fmaf(g_fb[NQ + r], ldbf(wo, (size_t)r * D_MODEL + c), a);
    for (int r = threadIdx.x; r < FF; r += 128) a = fmaf(g_fb[2 * NQ + r], ldbf(wd, (size_t)r * D_MODEL + c), a);
    a = fb_block_reduce(a, false, sh);
    if (threadIdx.x == 0) out[c] = (uint16_t)pack2(a + ldbf(x, c), 0.f);
}

typedef CUresult (*EncodeFn)(CUtensorMap*, CUtensorMapDataType, cuuint32_t, void*, const cuuint64_t*, const cuuint64_t*,
                             const cuuint32_t*, const cuuint32_t*, CUtensorMapInterleave, CUtensorMapSwizzle,
                             CUtensorMapL2promotion, CUtensorMapFloatOOBfill);

void make_map(EncodeFn fn, CUtensorMap* m, const void* p, int inner, int outer, int box_inner, int box_outer, CUtensorMapSwizzle sw) {
    cuuint64_t gd[2] = {(cuuint64_t)inner, (cuuint64_t)outer};
    cuuint64_t gs[1] = {(cuuint64_t)inner * 2};
    cuuint32_t bd[2] = {(cuuint32_t)box_inner, (cuuint32_t)box_outer};
    cuuint32_t es[2] = {1, 1};
    fn(m, CU_TENSOR_MAP_DATA_TYPE_BFLOAT16, 2, const_cast<void*>(p), gd, gs, bd, es, CU_TENSOR_MAP_INTERLEAVE_NONE,
       sw, CU_TENSOR_MAP_L2_PROMOTION_L2_128B, CU_TENSOR_MAP_FLOAT_OOB_FILL_NONE);
}

}

extern "C" void kernel_launch(void* const* d_in, const int* in_sizes, int n_in, void* d_out, int out_size) {
    (void)in_sizes; (void)n_in; (void)out_size;
    static int mode = -1;
    static EncodeFn enc_fn = nullptr;
    static void* scratch = nullptr;
    if (mode < 0) {
        cudaDriverEntryPointQueryResult qr;
        void* fn = nullptr;
        cudaGetDriverEntryPoint("cuTensorMapEncodeTiled", &fn, cudaEnableDefault, &qr);
        enc_fn = (EncodeFn)fn;
        cudaGetSymbolAddress(&scratch, g_scratch);
        int dev = 0, sms = 0, occ = 0;
        cudaGetDevice(&dev);
        cudaDeviceGetAttribute(&sms, cudaDevAttrMultiProcessorCount, dev);
        const bool ok = cudaFuncSetAttribute(fused_decode_kernel, cudaFuncAttributeMaxDynamicSharedMemorySize, SMEM_BYTES) == cudaSuccess &&
                        cudaOccupancyMaxActiveBlocksPerMultiprocessor(&occ, fused_decode_kernel, NTHREADS, SMEM_BYTES) == cudaSuccess;
        mode = ok && enc_fn && scratch && sms * occ >= NCTA;
        (void)cudaGetLastError();
    }
    if (!mode) {
        const uint16_t* const* in = (const uint16_t* const*)d_in;
        fb_proj<<<(NQ + FF) / 128, 128>>>(in[0], in[3], in[6], in[7]);
        fb_attn<<<32, 128>>>(in[1], in[2]);
        fb_out<<<D_MODEL, 128>>>(in[0], in[4], in[8], (uint16_t*)d_out);
        return;
    }
    Maps maps;
    make_map(enc_fn, &maps.m[0], d_in[6], FF, D_MODEL, 32, 144, CU_TENSOR_MAP_SWIZZLE_64B);
    make_map(enc_fn, &maps.m[1], d_in[7], FF, D_MODEL, 32, 144, CU_TENSOR_MAP_SWIZZLE_64B);
    make_map(enc_fn, &maps.m[2], d_in[8], 64, FF * 9, 64, 144, CU_TENSOR_MAP_SWIZZLE_128B);
    make_map(enc_fn, &maps.m[3], d_in[4], 64, NQ * 9, 64, 144, CU_TENSOR_MAP_SWIZZLE_128B);
    make_map(enc_fn, &maps.m[4], d_in[8], D_MODEL, FF, 16, 256, CU_TENSOR_MAP_SWIZZLE_32B);
    make_map(enc_fn, &maps.m[5], d_in[3], NQ, D_MODEL, 32, 144, CU_TENSOR_MAP_SWIZZLE_64B);
    fused_decode_kernel<<<NCTA, NTHREADS, SMEM_BYTES>>>(
        (const uint32_t*)d_in[0], (const uint8_t*)d_in[1], (const uint8_t*)d_in[2],
        (uint16_t*)d_out, (Scratch*)scratch, maps);
}
```

```cpp
#include <cuda_runtime.h>
#include <cuda_bf16.h>
#include <cuda.h>
#include <stdint.h>

namespace {

constexpr int D_MODEL = 576;
constexpr int SK = 65536;
constexpr int WIN = 4096;
constexpr int NQ = 4096;
constexpr int FF = 4608;
constexpr int NMAIN = 128;
constexpr int NCTA = 132;
constexpr int NRED = 36;
constexpr int NTHREADS = 352;
constexpr int PACE_W0 = 20000;
constexpr float PACE_NS = 0.0408f;
constexpr int C_DELAY = 400;
constexpr int DEPTH = 6;
constexpr int QPOLL_FROM = 3, OPOLL_FROM = 18, HPOLL_FROM = 21;
constexpr int NCU = 8;
constexpr int CU0 = NMAIN - NCU;
constexpr int CLINES = (16 + NCU) / 8;
constexpr uint32_t KV_BYTES = 16384;
constexpr uint32_t IT_BYTES = 18432;
constexpr uint32_t WQ_OFF = 176128;
constexpr uint32_t MISC_OFF = 212992;
constexpr uint32_t OFF_FULL = MISC_OFF;
constexpr uint32_t OFF_EMPTY = MISC_OFF + 256;
constexpr uint32_t OFF_XN = MISC_OFF + 512;
constexpr uint32_t OFF_RED = OFF_XN + 1152;
constexpr uint32_t OFF_Q = OFF_RED + 9216;
constexpr uint32_t OFF_S = OFF_Q + 512;
constexpr uint32_t OFF_P = OFF_S + 4096;
constexpr uint32_t OFF_OEX = OFF_P + 2048;
constexpr uint32_t OFF_ML = OFF_OEX + 128;
constexpr uint32_t OFF_EP = OFF_ML + 128;
constexpr uint32_t OFF_HX = OFF_EP + 16;
constexpr uint32_t OFF_FIN = OFF_P;
constexpr uint32_t SMEM_BYTES = OFF_HX + (16 + NCU) * 64;
static_assert(SMEM_BYTES <= 232448, "smem");

constexpr uint32_t SPIN_LIMIT = 1u << 20;

struct Scratch {
    uint4 q[16][64];
    uint32_t opart[16][8][8 * 32];
    uint4 hx[16 + NCU][8];
    uint4 outpart[NRED][NMAIN * 4];
    uint32_t epoch[NCTA][32];
};
__device__ __align__(128) Scratch g_scratch;

struct Maps { CUtensorMap m[6]; };

__device__ __forceinline__ uint32_t gtime32() { uint32_t t; asm volatile("mov.u32 %0, %globaltimer_lo;" : "=r"(t)); return t; }

__device__ __forceinline__ uint32_t s2u(const void* p) { return (uint32_t)__cvta_generic_to_shared(p); }
__device__ __forceinline__ void mbar_init(uint32_t a, uint32_t c) { asm volatile("mbarrier.init.shared::cta.b64 [%0], %1;" ::"r"(a), "r"(c) : "memory"); }
__device__ __forceinline__ void mbar_expect(uint32_t a, uint32_t b) { asm volatile("mbarrier.arrive.expect_tx.shared::cta.b64 _, [%0], %1;" ::"r"(a), "r"(b) : "memory"); }
__device__ __forceinline__ void mbar_wait(uint32_t a) {
    uint32_t ok, n = 0;
    do {
        asm volatile("{\n.reg .pred p;\nmbarrier.try_wait.parity.shared::cta.b64 p, [%1], 0;\nselp.u32 %0, 1, 0, p;\n}" : "=r"(ok) : "r"(a) : "memory");
        if (++n > SPIN_LIMIT) __trap();
    } while (!ok);
}
__device__ __forceinline__ bool mbar_test(uint32_t a) {
    uint32_t ok;
    asm volatile("{\n.reg .pred p;\nmbarrier.test_wait.parity.shared::cta.b64 p, [%1], 0;\nselp.u32 %0, 1, 0, p;\n}" : "=r"(ok) : "r"(a) : "memory");
    return ok;
}
__device__ __forceinline__ uint64_t policy_evict_first() { uint64_t p; asm("createpolicy.fractional.L2::evict_first.b64 %0, 1.0;" : "=l"(p)); return p; }
__device__ __forceinline__ uint64_t policy_evict_normal() { uint64_t p; asm("createpolicy.fractional.L2::evict_normal.b64 %0, 1.0;" : "=l"(p)); return p; }
__device__ __forceinline__ void bulk_ld(uint32_t dst, const void* src, uint32_t bytes, uint32_t bar, uint64_t pol) {
    asm volatile("cp.async.bulk.shared::cluster.global.mbarrier::complete_tx::bytes.L2::cache_hint [%0], [%1], %2, [%3], %4;"
                 ::"r"(dst), "l"(src), "r"(bytes), "r"(bar), "l"(pol) : "memory");
}
__device__ __forceinline__ void tma2d_ld(uint32_t dst, const CUtensorMap* m, int c0, int c1, uint32_t bar, uint64_t pol) {
    asm volatile("cp.async.bulk.tensor.2d.shared::cluster.global.mbarrier::complete_tx::bytes.L2::cache_hint [%0], [%1, {%3, %4}], [%2], %5;"
                 ::"r"(dst), "l"(m), "r"(bar), "r"(c0), "r"(c1), "l"(pol) : "memory");
}
__device__ __forceinline__ uint4 lds128(uint32_t a) { uint4 v; asm volatile("ld.shared.v4.u32 {%0,%1,%2,%3}, [%4];" : "=r"(v.x), "=r"(v.y), "=r"(v.z), "=r"(v.w) : "r"(a) : "memory"); return v; }
__device__ __forceinline__ float4 lds128f(uint32_t a) { float4 v; asm volatile("ld.shared.v4.f32 {%0,%1,%2,%3}, [%4];" : "=f"(v.x), "=f"(v.y), "=f"(v.z), "=f"(v.w) : "r"(a) : "memory"); return v; }
__device__ __forceinline__ uint32_t lds32(uint32_t a) { uint32_t v; asm volatile("ld.shared.u32 %0, [%1];" : "=r"(v) : "r"(a) : "memory"); return v; }
__device__ __forceinline__ float lds32f(uint32_t a) { float v; asm volatile("ld.shared.f32 %0, [%1];" : "=f"(v) : "r"(a) : "memory"); return v; }
__device__ __forceinline__ uint4 ldsm4t(uint32_t a) {
    uint4 v;
    asm volatile("ldmatrix.sync.aligned.m8n8.x4.trans.shared.b16 {%0,%1,%2,%3}, [%4];" : "=r"(v.x), "=r"(v.y), "=r"(v.z), "=r"(v.w) : "r"(a) : "memory");
    return v;
}
__device__ __forceinline__ void mma16(float (&c)[4], uint32_t a0, uint32_t a1, uint32_t a2, uint32_t a3, uint32_t b0, uint32_t b1) {
    asm volatile("mma.sync.aligned.m16n8k16.row.col.f32.bf16.bf16.f32 {%0,%1,%2,%3}, {%4,%5,%6,%7}, {%8,%9}, {%0,%1,%2,%3};"
                 : "+f"(c[0]), "+f"(c[1]), "+f"(c[2]), "+f"(c[3]) : "r"(a0), "r"(a1), "r"(a2), "r"(a3), "r"(b0), "r"(b1));
}
__device__ __forceinline__ void mma8(float (&c)[4], uint32_t a0, uint32_t a1, uint32_t b0) {
    asm volatile("mma.sync.aligned.m16n8k8.row.col.f32.bf16.bf16.f32 {%0,%1,%2,%3}, {%4,%5}, {%6}, {%0,%1,%2,%3};"
                 : "+f"(c[0]), "+f"(c[1]), "+f"(c[2]), "+f"(c[3]) : "r"(a0), "r"(a1), "r"(b0));
}
__device__ __forceinline__ uint32_t ldg_nc32(const void* p) { uint32_t v; asm volatile("ld.global.nc.u32 %0, [%1];" : "=r"(v) : "l"(p)); return v; }
__device__ __forceinline__ uint32_t ld_rlx(const uint32_t* p) { uint32_t v; asm volatile("ld.relaxed.gpu.global.u32 %0, [%1];" : "=r"(v) : "l"(p) : "memory"); return v; }
__device__ __forceinline__ uint4 ld_rlx128(const uint4* p) { uint4 v; asm volatile("ld.relaxed.gpu.global.v4.u32 {%0,%1,%2,%3}, [%4];" : "=r"(v.x), "=r"(v.y), "=r"(v.z), "=r"(v.w) : "l"(p) : "memory"); return v; }
__device__ __forceinline__ void ld_rlx128_p(uint4& v, const uint4* p, uint32_t en) {
    asm volatile("{\n.reg .pred p;\nsetp.ne.u32 p, %5, 0;\n@p ld.relaxed.gpu.global.v4.u32 {%0,%1,%2,%3}, [%4];\n}"
                 : "+r"(v.x), "+r"(v.y), "+r"(v.z), "+r"(v.w) : "l"(p), "r"(en) : "memory");
}
__device__ __forceinline__ void st_rlx64(uint32_t* p, uint32_t a, uint32_t b) { asm volatile("st.relaxed.gpu.global.v2.u32 [%0], {%1,%2};" ::"l"(p), "r"(a), "r"(b) : "memory"); }

__device__ __forceinline__ float bf_lo(uint32_t u) { return __uint_as_float(u << 16); }
__device__ __forceinline__ float bf_hi(uint32_t u) { return __uint_as_float(u & 0xffff0000u); }
__device__ __forceinline__ uint32_t pack2(float lo, float hi) { uint32_t r; asm("cvt.rn.bf16x2.f32 %0, %1, %2;" : "=r"(r) : "f"(hi), "f"(lo)); return r; }
__device__ __forceinline__ float bfr(float v) { return __uint_as_float(pack2(0.f, v)); }
__device__ __forceinline__ float shx(float v, int o) { return __shfl_xor_sync(0xffffffffu, v, o); }
__device__ __forceinline__ uint32_t hi2(uint32_t a, uint32_t b) { return __byte_perm(a, b, 0x7632); }

__device__ __forceinline__ void sts32_p(bool en, uint32_t a, uint32_t v) {
    asm volatile("{\n.reg .pred p;\nsetp.ne.u32 p, %2, 0;\n@p st.shared.u32 [%0], %1;\n}" ::"r"(a), "r"(v), "r"((uint32_t)en) : "memory");
}
__device__ __forceinline__ void sts64_p(bool en, uint32_t a, uint32_t x, uint32_t y) {
    asm volatile("{\n.reg .pred p;\nsetp.ne.u32 p, %3, 0;\n@p st.shared.v2.u32 [%0], {%1,%2};\n}" ::"r"(a), "r"(x), "r"(y), "r"((uint32_t)en) : "memory");
}
__device__ __forceinline__ void st_rlx_p(bool en, uint32_t* p, uint32_t v) {
    asm volatile("{\n.reg .pred p;\nsetp.ne.u32 p, %2, 0;\n@p st.relaxed.gpu.global.u32 [%0], %1;\n}" ::"l"(p), "r"(v), "r"((uint32_t)en) : "memory");
}
__device__ __forceinline__ void mbar_arrive_p(bool en, uint32_t a) {
    asm volatile("{\n.reg .pred p;\nsetp.ne.u32 p, %1, 0;\n@p mbarrier.arrive.shared::cta.b64 _, [%0];\n}" ::"r"(a), "r"((uint32_t)en) : "memory");
}
__device__ __forceinline__ void warp_release(bool en, uint32_t a) {
    __syncwarp();
    mbar_arrive_p(en && (threadIdx.x & 31) == 0, a);
}
__device__ __forceinline__ uint32_t lop_ne(uint32_t a, uint32_t b, uint32_t c) { uint32_t r; asm("lop3.b32 %0, %1, %2, %3, 0x7E;" : "=r"(r) : "r"(a), "r"(b), "r"(c)); return r; }
__device__ __forceinline__ uint32_t stale(const uint4& v, uint32_t tg) { return (lop_ne(v.x, v.y, tg) | lop_ne(v.z, v.w, tg)) & 1u; }
__device__ __forceinline__ float selp(float a, float b, uint32_t c) { float r; asm("{\n.reg .pred p;\nsetp.ne.u32 p, %3, 0;\nselp.f32 %0, %1, %2, p;\n}" : "=f"(r) : "f"(a), "f"(b), "r"(c)); return r; }
__device__ __forceinline__ float sel4(float a0, float a1, float a2, float a3, uint32_t i) { return selp(selp(a3, a2, i & 1), selp(a1, a0, i & 1), i & 2); }
#define F2U __float_as_uint
#define U2F __uint_as_float
#define BAR_COMP(id) asm volatile("bar.sync " #id ", 288;" ::: "memory")
#define ZERO44(A) _Pragma("unroll") for (int i_ = 0; i_ < 4; i_++) { A[i_][0] = 0.f; A[i_][1] = 0.f; A[i_][2] = 0.f; A[i_][3] = 0.f; }

__global__ void __launch_bounds__(NTHREADS, 1)
fused_decode_kernel(const uint32_t* __restrict__ x32, const uint8_t* __restrict__ kc, const uint8_t* __restrict__ vc,
                    uint16_t* __restrict__ out16, Scratch* sc, const __grid_constant__ Maps maps) {
    extern __shared__ __align__(1024) uint8_t smem[];
    const uint32_t sb = s2u(smem);
    const int lane = threadIdx.x & 31, wid = threadIdx.x >> 5;
    const int b = blockIdx.x, h = b >> 3, s = b & 7;
    const bool is_main = b < NMAIN, is_red = b < NRED;
    const uint32_t full = sb + OFF_FULL, empty = sb + OFF_EMPTY;
    const uint32_t bar_q = sb + OFF_FULL + 27 * 8, bar_o = bar_q + 8, bar_h = bar_q + 16;
    const size_t kvoff = ((size_t)h * SK + (SK - WIN) + s * 64) * 256;

    if (threadIdx.x == 0) {
        mbar_init(full, 1);
        if (is_main) {
            mbar_expect(full, KV_BYTES);
            bulk_ld(sb, kc + kvoff, KV_BYTES, full, policy_evict_first());
        }
    }
    if (threadIdx.x == 32 && is_main) {
#pragma unroll
        for (int i = 0; i < 2; i++) {
            mbar_init(full + (25 + i) * 8, 1);
            mbar_expect(full + (25 + i) * 8, IT_BYTES);
            tma2d_ld(sb + WQ_OFF + i * IT_BYTES, &maps.m[5], b * 32, i * 288, full + (25 + i) * 8, policy_evict_normal());
            tma2d_ld(sb + WQ_OFF + i * IT_BYTES + 9216, &maps.m[5], b * 32, i * 288 + 144, full + (25 + i) * 8, policy_evict_normal());
        }
    }
    if (wid == 0) {
        const uint32_t t_start = gtime32() - 150;
        if (lane == 0) {
#pragma unroll
            for (int i = 1; i < 25; i++) mbar_init(full + i * 8, 1);
            mbar_init(bar_q, 33);
            mbar_init(bar_o, 32);
            mbar_init(bar_h, 32);
            const uint32_t cnt = is_main ? 8 : 9;
#pragma unroll
            for (int i = 0; i < 13; i++) mbar_init(empty + i * 8, cnt);
            mbar_init(empty + 13 * 8, 9);
        }
        __syncwarp();
        asm volatile("bar.arrive 15, %0;" ::"n"(NTHREADS) : "memory");
        const int i = lane;
        const int j = is_main ? i - 16 : i & 3;
        const int unit = is_main ? b : NMAIN + (b - NMAIN) * 4 + (i >> 2);
        const uint32_t off = !is_main ? (i % 11) * IT_BYTES : i < 12 ? i * KV_BYTES : i < 16 ? (i - 12) * KV_BYTES : i < 24 ? 65536u + (i - 16) * IT_BYTES : 0u;
        const int dep = is_main ? (i < 10 ? -1 : i < 12 ? 13 : i < 16 ? i - 12 : i < 24 ? min(i - 11, 11) : 12) : i - 11;
        const bool skipd = is_main && b >= CU0;
        const int prev = i == 24 ? 21 : i - DEPTH;
        const uint32_t esc = full + (skipd && i == 22 ? 19 : max(i - 1, 0)) * 8;
        const uint8_t* src = (i < 8 ? kc : vc) + kvoff + (i & 7) * (8 * KV_BYTES);
        const CUtensorMap* mp = &maps.m[j < 4 ? 0 : min(j >> 1, 4)];
        const int c0 = j < 4 ? unit * 32 : j < 8 ? 0 : b * 16;
        const int c1 = j < 4 ? j * 144 : j < 8 ? unit * 288 + (j & 1) * 144 : CU0 * 32;
        const uint32_t dst = sb + off, bar = full + i * 8;
        const uint64_t pol = (j < 0 || (j >= 4 && j < 8)) ? policy_evict_first() : policy_evict_normal();
        const int i0 = is_main ? 1 : 0, i1 = is_red ? 25 : is_main ? 24 : 16;
        const int cum = is_main ? 2 * IT_BYTES + (i < 16 ? i * KV_BYTES : 16 * KV_BYTES + (i - 16) * IT_BYTES) : i * IT_BYTES;
        int t_rel = (int)((float)(cum - PACE_W0 + b * 128) * PACE_NS);
        if (i >= i0 && i < i1) mbar_expect(bar, j < 0 ? KV_BYTES : j == 8 ? CLINES * 8192 : IT_BYTES);
        if (lane >= 27) asm volatile("prefetch.tensormap [%0];" ::"l"(&maps.m[lane - 27]) : "memory");
#pragma unroll 1
        for (int k = i0; k < i1; k++) {
            if (lane == k && !(skipd && (k == 20 || k == 21))) {
                if (prev >= 0) mbar_wait(full + prev * 8);
                if (dep >= 0) mbar_wait(empty + dep * 8);
                if (k == 24) t_rel = (int)(gtime32() - t_start) + C_DELAY;
                while ((int)(gtime32() - t_start) < t_rel && !mbar_test(esc)) {}
                if (j < 0) {
                    bulk_ld(dst, src, KV_BYTES, bar, pol);
                } else {
                    tma2d_ld(dst, mp, c0, c1, bar, pol);
                    if (j < 4) tma2d_ld(dst + 9216, mp + 1, c0, c1, bar, pol);
                    if (j == 8) {
#pragma unroll
                        for (int q = 1; q < CLINES; q++) tma2d_ld(dst + q * 8192, mp, c0, c1 + q * 256, bar, pol);
                    }
                }
            }
            __syncwarp();
        }
        return;
    }
    if (wid == 1) {
        __syncwarp();
        asm volatile("bar.sync 15, %0;" ::"n"(NTHREADS) : "memory");
        if (!is_main) return;
        const uint32_t tg = ~lds32(sb + OFF_EP) & 1u;
        uint32_t n = 0;
        {
            mbar_wait(full + QPOLL_FROM * 8);
            uint4 a, c;
            for (;;) {
                a = ld_rlx128(&sc->q[h][lane * 2]);
                c = ld_rlx128(&sc->q[h][lane * 2 + 1]);
                if (!__any_sync(0xffffffffu, stale(a, tg) | stale(c, tg))) break;
                if (++n > SPIN_LIMIT) __trap();
                __nanosleep(100);
            }
            asm volatile("st.shared.v4.u32 [%0], {%1,%2,%3,%4};" ::"r"(sb + OFF_Q + lane * 16), "r"(hi2(a.x, a.y)), "r"(hi2(a.z, a.w)),
                         "r"(hi2(c.x, c.y)), "r"(hi2(c.z, c.w)) : "memory");
            mbar_arrive_p(true, bar_q);
        }
        {
            const uint32_t* slot = &sc->opart[h][s][lane];
            mbar_wait(full + OPOLL_FROM * 8);
            uint32_t ov[8];
            for (;;) {
                uint32_t bad = 0;
#pragma unroll
                for (int i = 0; i < 8; i++) { ov[i] = ld_rlx(slot + i * 32); bad |= ov[i] ^ tg; }
                if (__all_sync(0xffffffffu, !(bad & 1u))) break;
                if (++n > SPIN_LIMIT) __trap();
                __nanosleep(100);
            }
            float lse[8], M = -INFINITY;
#pragma unroll
            for (int i = 0; i < 8; i++) { lse[i] = U2F(__ballot_sync(0xffffffffu, ov[i] & 2u)); M = fmaxf(M, lse[i]); }
            float o = 0.f, L = 0.f;
#pragma unroll
            for (int i = 0; i < 8; i++) {
                const float e = __expf(lse[i] - M);
                o = fmaf(e, U2F(ov[i]), o);
                L += e;
            }
            o = __fdividef(o, L);
            sts32_p(true, sb + OFF_OEX + lane * 4, pack2(o, __shfl_down_sync(0xffffffffu, o, 1)));
            mbar_arrive_p(true, bar_o);
        }
        if (is_red) {
            mbar_wait(full + HPOLL_FROM * 8);
            uint4 hv[2 * CLINES];
            for (;;) {
                uint32_t bad = 0;
#pragma unroll
                for (int i = 0; i < 2 * CLINES; i++) { hv[i] = ld_rlx128(&sc->hx[0][0] + i * 32 + lane); bad |= stale(hv[i], tg); }
                if (!__any_sync(0xffffffffu, bad)) break;
                if (++n > SPIN_LIMIT) __trap();
                __nanosleep(100);
            }
#pragma unroll
            for (int i = 0; i < 2 * CLINES; i++) sts64_p(true, sb + OFF_HX + i * 256 + lane * 8, hi2(hv[i].x, hv[i].y), hi2(hv[i].z, hv[i].w));
            mbar_arrive_p(true, bar_h);
        }
        return;
    }

    const int w = wid - 2, t = threadIdx.x - 64;
    const int g = lane >> 2, tq = lane & 3;
    float xres;
    {
        const uint32_t xr = ldg_nc32(x32 + (is_red ? b : 0) * 8 + (lane >> 1 & 7));
        xres = (lane & 1) ? bf_hi(xr) : bf_lo(xr);
        uint32_t xa[9];
#pragma unroll
        for (int i = 0; i < 9; i++) xa[i] = ldg_nc32(x32 + i * 32 + lane);
        const uint32_t xmine = ldg_nc32(x32 + t);
        if (t == 0) {
            const uint32_t e = sc->epoch[b][0];
            sc->epoch[b][0] = e + 1;
            sts32_p(true, sb + OFF_EP, e);
        }
        float sum = 0.f;
#pragma unroll
        for (int i = 0; i < 9; i++) sum += bf_lo(xa[i]) + bf_hi(xa[i]);
#pragma unroll
        for (int o = 16; o; o >>= 1) sum += shx(sum, o);
        const float mean = sum * (1.0f / D_MODEL);
        float sq = 0.f;
#pragma unroll
        for (int i = 0; i < 9; i++) { float a = bf_lo(xa[i]) - mean, c = bf_hi(xa[i]) - mean; sq = fmaf(a, a, fmaf(c, c, sq)); }
#pragma unroll
        for (int o = 16; o; o >>= 1) sq += shx(sq, o);
        const float m_bf = bfr(mean);
        const float sd = bfr(sqrtf(bfr(bfr(sq * (1.0f / D_MODEL)) + 1e-5f)));
        sts32_p(true, sb + OFF_XN + t * 4, pack2(bfr(bf_lo(xmine) - m_bf) / sd, bfr(bf_hi(xmine) - m_bf) / sd));
        asm volatile("bar.sync 15, %0;" ::"n"(NTHREADS) : "memory");
    }

    const uint32_t ep = lds32(sb + OFF_EP), tg = ~ep & 1u;
    const int lrow = (lane >> 4) * 8 + (lane & 7), lc = lane >> 3 & 1;
    const uint32_t gu0 = sb + (w * 16 + lrow) * 64 + (lc ^ (lrow >> 1 & 3)) * 16;
    const uint32_t xaddr = sb + OFF_XN + w * 32 + tq * 4;

    auto col_item = [&](float (&ga)[4][4], uint32_t off, uint32_t bar, int ra, int rb) {
        const uint32_t xA = xaddr + ra * 288, xB = xaddr + rb * 288;
        const uint32_t b0 = lds32(xA), b1 = lds32(xA + 16), b2 = lds32(xB), b3 = lds32(xB + 16);
        mbar_wait(bar);
#pragma unroll
        for (int i = 0; i < 4; i++) {
            const uint4 a = ldsm4t((gu0 ^ ((i & 1) * 32)) + off + (i >> 1) * 9216);
            mma16(ga[i], a.x, a.y, a.z, a.w, i < 2 ? b0 : b2, i < 2 ? b1 : b3);
        }
    };
    auto col_reduce = [&](float (&ga)[4][4], uint32_t red, float& gg, float& uu, bool rd) {
        const float v0 = sel4(ga[0][0], ga[1][0], ga[2][0], ga[3][0], tq), v1 = sel4(ga[0][2], ga[1][2], ga[2][2], ga[3][2], tq);
        sts32_p(true, red + w * 256 + tq * 64 + g * 4, F2U(v0));
        sts32_p(true, red + w * 256 + tq * 64 + g * 4 + 32, F2U(v1));
        BAR_COMP(3);
        gg = 0.f; uu = 0.f;
        if (rd) {
#pragma unroll
            for (int k = 0; k < 9; k++) { gg += lds32f(red + k * 256 + lane * 4); uu += lds32f(red + k * 256 + 128 + lane * 4); }
        }
    };
    auto geglu = [&](float gg, float uu) {
        gg = bfr(gg); uu = bfr(uu);
        const float inner = 0.7978845608028654f * (gg + 0.044715f * gg * gg * gg);
        const float hv = bfr(__fdividef(gg, 1.0f + __expf(-2.0f * inner))) * uu;
        return pack2(hv, __shfl_down_sync(0xffffffffu, hv, 1));
    };

    if (!is_main) {
        int it = 0;
        uint32_t off = 0;
#pragma unroll 1
        for (int u = 0; u < 4; u++) {
            float ga[4][4], gg, uu;
            ZERO44(ga)
#pragma unroll 1
            for (int j = 0; j < 4; j++) {
                col_item(ga, off, full + it * 8, j, j);
                warp_release(it < 5, empty + it * 8);
                it++; off = off == 10 * IT_BYTES ? 0u : off + IT_BYTES;
            }
            col_reduce(ga, sb + OFF_RED + (u & 1) * 2304, gg, uu, w == 8);
            const uint32_t hp = geglu(gg, uu);
            st_rlx_p(w == 8, reinterpret_cast<uint32_t*>(&sc->hx[NCU + (b - NMAIN) * 4 + u][0]) + (lane >> 1 & 3) * 8 + (lane >> 3) * 2 + (lane & 1), hp << 16 | tg);
        }
        return;
    }

    uint32_t* outp = reinterpret_cast<uint32_t*>(__shfl_sync(0xffffffffu, reinterpret_cast<unsigned long long>(
                         reinterpret_cast<uint32_t*>(&sc->outpart[w * 4 + tq][b * 4]) + g * 2), lane));
    const int redw = __shfl_sync(0xffffffffu, is_red ? w : -1, lane);
    st_rlx64(outp, ep, ep);
    st_rlx_p(w < 8, &sc->opart[h][w & 7][s * 32 + lane], ep);
    st_rlx_p(w == 8, reinterpret_cast<uint32_t*>(&sc->q[h][s * 8]) + lane, ep);
    st_rlx_p(w == 8 && b >= CU0, reinterpret_cast<uint32_t*>(&sc->hx[max(b - CU0, 0)][0]) + lane, ep);
    float ga[4][4], gg, uu;
    ZERO44(ga)
    col_item(ga, WQ_OFF, full + 25 * 8, 0, 1);
    col_item(ga, WQ_OFF + IT_BYTES, full + 26 * 8, 2, 3);
    warp_release(true, empty + 13 * 8);
    col_reduce(ga, sb + OFF_RED, gg, uu, w == 8);
    st_rlx_p(w == 8, reinterpret_cast<uint32_t*>(&sc->q[h][s * 8]) + lane, pack2(0.f, gg + uu) | tg);
    warp_release(w == 8, bar_q);
    if (w < 8) {
        mbar_wait(bar_q);
        uint4 qf[4];
#pragma unroll
        for (int j = 0; j < 4; j++) qf[j] = lds128(sb + OFF_Q + (g & 1) * 256 + ((j ^ (g >> 1 & 1)) * 4 + tq) * 16);
        const uint32_t koff = sb + (w * 8 + g) * 256 + tq * 16;
        const uint32_t kx = (g & 1) * 64;
        const uint32_t sw = sb + OFF_S + w * 512, pw = sb + OFF_P + w * 256;
        float m = -INFINITY;
#pragma unroll 2
        for (int c = 0; c < 8; c++) {
            mbar_wait(full + c * 8);
            uint4 kv[4];
#pragma unroll
            for (int j = 0; j < 4; j++) kv[j] = lds128(koff + c * KV_BYTES + ((j * 64) ^ kx));
            float c0[4] = {0.f, 0.f, 0.f, 0.f}, c1[4] = {0.f, 0.f, 0.f, 0.f};
#pragma unroll
            for (int j = 0; j < 4; j++) {
                mma16(c0, qf[j].x, qf[j].x, qf[j].y, qf[j].y, kv[j].x, kv[j].y);
                mma16(c1, qf[j].z, qf[j].z, qf[j].w, qf[j].w, kv[j].z, kv[j].w);
            }
            warp_release(true, empty + c * 8);
            const float raw = (g & 2) ? c0[1] + c1[1] : c0[0] + c1[0];
            const float scv = bfr(bfr(raw) * 0.08838834764831845f);
            m = fmaxf(m, scv);
            sts32_p(g < 4, sw + c * 64 + (g & 1) * 32 + tq * 8 + (g & 2) * 2, F2U(scv));
        }
        m = fmaxf(m, shx(m, 1)); m = fmaxf(m, shx(m, 2)); m = fmaxf(m, shx(m, 8));
        __syncwarp();
        {
            const float mh = __shfl_sync(0xffffffffu, m, (lane & 2) * 2);
            const float4 sv = lds128f(sw + lane * 16);
            const uint32_t p01 = pack2(__expf(sv.x - mh), __expf(sv.y - mh)), p23 = pack2(__expf(sv.z - mh), __expf(sv.w - mh));
            sts64_p(true, pw + lane * 8, p01, p23);
            float l = (bf_lo(p01) + bf_hi(p01)) + (bf_lo(p23) + bf_hi(p23));
            l += shx(l, 1); l += shx(l, 4); l += shx(l, 8); l += shx(l, 16);
            sts64_p((lane & 29) == 0, sb + OFF_ML + (lane >> 1) * 64 + w * 8, F2U(mh), F2U(l));
        }
        __syncwarp();
        float oc[8][4];
#pragma unroll
        for (int i = 0; i < 8; i++) { oc[i][0] = 0.f; oc[i][1] = 0.f; oc[i][2] = 0.f; oc[i][3] = 0.f; }
        const uint32_t voff = sb + (w * 8 + (lane & 7)) * 256;
        const uint32_t vx = ((lane >> 3) ^ (lane & 6)) * 16;
#pragma unroll 1
        for (int c = 0; c < 8; c++) {
            uint32_t pb = lds32(pw + c * 32 + (g & 1) * 16 + tq * 4);
            pb = (g >> 1) == tq ? pb : 0u;
            mbar_wait(full + (8 + c) * 8);
            const uint32_t vb = voff + (c < 4 ? c + 8 : c - 4) * KV_BYTES;
#pragma unroll
            for (int j = 0; j < 4; j++) {
                const uint4 a = ldsm4t(vb + ((j * 64) ^ vx));
                mma8(oc[2 * j], a.x, a.y, pb);
                mma8(oc[2 * j + 1], a.z, a.w, pb);
            }
            warp_release(c < 4 || c == 5, empty + min(8 + c, 12) * 8);
        }
#pragma unroll
        for (int i = 0; i < 8; i += 2)
#pragma unroll
            for (int e = 0; e < 4; e++) oc[i][e] += shx(oc[i + 1][e], 1);
#pragma unroll
        for (int i = 0; i < 8; i += 4)
#pragma unroll
            for (int e = 0; e < 4; e++) {
                oc[i][e] += shx(oc[i + 2][e], 2);
                sts32_p(true, sb + OFF_RED + w * 1024 + (e & 1) * 512 + ((2 * i + (e >> 1)) ^ (2 * tq)) * 32 + g * 4, F2U(oc[i][e]));
            }
    }
    BAR_COMP(2);
    if (w < 8) {
        const uint32_t ml = sb + OFF_ML + (t >> 7) * 64;
        float mm[8], ll[8];
#pragma unroll
        for (int i = 0; i < 4; i++) { float4 a = lds128f(ml + i * 16); mm[2 * i] = a.x; ll[2 * i] = a.y; mm[2 * i + 1] = a.z; ll[2 * i + 1] = a.w; }
        float M = mm[0];
#pragma unroll
        for (int i = 1; i < 8; i++) M = fmaxf(M, mm[i]);
        float o = 0.f, L = 0.f;
#pragma unroll
        for (int i = 0; i < 8; i++) {
            float e = __expf(mm[i] - M);
            o = fmaf(e, lds32f(sb + OFF_RED + i * 1024 + t * 4), o);
            L = fmaf(e, ll[i], L);
        }
        const uint32_t lse = F2U(M + __logf(L));
        st_rlx_p(true, &sc->opart[h][w][s * 32 + lane], (F2U(__fdividef(o, L)) & ~3u) | ((lse >> lane & 1u) << 1) | tg);
    }
    ZERO44(ga)
#pragma unroll
    for (int j = 0; j < 4; j++) col_item(ga, 65536u + j * IT_BYTES, full + (16 + j) * 8, j, j);
    col_reduce(ga, sb + OFF_S, gg, uu, true);
    const uint32_t hp = geglu(gg, uu);

    float acc[4][4];
    ZERO44(acc)
    uint32_t rw[4];
#pragma unroll
    for (int i = 0; i < 4; i++) rw[i] = __shfl_sync(0xffffffffu, sb + (lrow * 9 + w) * 128 + ((i * 32) ^ ((lc ^ ((lrow + w) & 7)) * 16)), lane);
    auto row_item = [&](uint32_t off, uint32_t bar, uint32_t cp, int r0) {
        const uint32_t b0 = __shfl_sync(0xffffffffu, cp, r0 + tq * 2), b1 = __shfl_sync(0xffffffffu, cp, r0 + tq * 2 + 8);
        mbar_wait(bar);
#pragma unroll
        for (int i = 0; i < 4; i++) {
            const uint4 a = ldsm4t(rw[i] + off);
            mma16(acc[i], a.x, a.y, a.z, a.w, b0, b1);
        }
    };
    if (b < CU0) {
        row_item(65536u + 4 * IT_BYTES, full + 20 * 8, hp, 0);
        row_item(65536u + 5 * IT_BYTES, full + 21 * 8, hp, 16);
    } else {
        st_rlx_p(w == 8, reinterpret_cast<uint32_t*>(&sc->hx[b - CU0][0]) + (lane >> 1 & 3) * 8 + (lane >> 3) * 2 + (lane & 1), hp << 16 | tg);
    }
    const uint4* slot = &sc->outpart[is_red ? b : 0][t & 255];
    uint32_t l4 = lane & 4, l8 = lane & 8;
    uint32_t fin_st = sb + OFF_FIN + (tq * 2 + (lane >> 2 & 1) + (lane & 8)) * 80 + w * 4;
    mbar_wait(bar_o);
    const uint32_t op = lds32(sb + OFF_OEX + lane * 4);
    row_item(65536u + 6 * IT_BYTES, full + 22 * 8, op, 0);
    row_item(65536u + 7 * IT_BYTES, full + 23 * 8, op, 16);
    {
        const float v0 = sel4(acc[0][0], acc[1][0], acc[2][0], acc[3][0], tq), v1 = sel4(acc[0][2], acc[1][2], acc[2][2], acc[3][2], tq);
        st_rlx64(outp, (F2U(v0) & ~1u) | tg, (F2U(v1) & ~1u) | tg);
    }
    if (redw < 0) return;
    if (redw < 8) {
        uint4 fa = make_uint4(ep, ep, ep, ep), fb = fa;
        {
            float c0[4] = {0.f, 0.f, 0.f, 0.f}, c1[4] = {0.f, 0.f, 0.f, 0.f};
            const uint32_t cb = sb + (w * (32 * CLINES) + lrow) * 32 + (lc ^ (lrow >> 2 & 1)) * 16;
            mbar_wait(bar_h);
            uint4 hb[CLINES];
#pragma unroll
            for (int i = 0; i < CLINES; i++) hb[i] = lds128(sb + OFF_HX + (w * CLINES + i) * 64 + tq * 16);
            mbar_wait(full + 24 * 8);
#pragma unroll
            for (int i = 0; i < CLINES; i++) {
                const uint4 a = ldsm4t(cb + i * 1024), e = ldsm4t(cb + i * 1024 + 512);
                mma16(c0, a.x, a.y, a.z, a.w, hb[i].x, hb[i].y);
                mma16(c1, e.x, e.y, e.z, e.w, hb[i].z, hb[i].w);
            }
            sts32_p(tq < 2, sb + OFF_FIN + (g + tq * 8) * 80 + 32 + w * 4, F2U(selp(c0[2] + c1[2], c0[0] + c1[0], tq)));
        }
        for (uint32_t n = 0;; n++) {
            const uint32_t sa = stale(fa, tg), sb2 = stale(fb, tg);
            if (!(sa | sb2)) break;
            ld_rlx128_p(fa, slot, sa);
            ld_rlx128_p(fb, slot + 256, sb2);
            if (n > SPIN_LIMIT) __trap();
        }
        __syncwarp();
        const float x0 = U2F(fa.x) + U2F(fb.x), x1 = U2F(fa.y) + U2F(fb.y), x2 = U2F(fa.z) + U2F(fb.z), x3 = U2F(fa.w) + U2F(fb.w);
        const float k0 = selp(x2, x0, l4) + shx(selp(x0, x2, l4), 4);
        const float k1 = selp(x3, x1, l4) + shx(selp(x1, x3, l4), 4);
        float k = selp(k1, k0, l8) + shx(selp(k0, k1, l8), 8);
        k += shx(k, 16);
        sts32_p(true, fin_st, F2U(k));
        asm volatile("bar.arrive 4, 288;" ::: "memory");
    } else {
        const uint32_t fa_ = __shfl_sync(0xffffffffu, sb + OFF_FIN + (lane & 15) * 80, lane);
        uint16_t* op16 = reinterpret_cast<uint16_t*>(__shfl_sync(0xffffffffu, reinterpret_cast<unsigned long long>(out16 + b * 16 + (lane & 15)), lane));
        asm volatile("bar.sync 4, 288;" ::: "memory");
        const float4 p0 = lds128f(fa_), p1 = lds128f(fa_ + 16), p2 = lds128f(fa_ + 32), p3 = lds128f(fa_ + 48);
        const float r = ((((p0.x + p0.y) + (p0.z + p0.w)) + ((p1.x + p1.y) + (p1.z + p1.w))) +
                         (((p2.x + p2.y) + (p2.z + p2.w)) + ((p3.x + p3.y) + (p3.z + p3.w)))) + xres;
        if (lane < 16) asm volatile("st.global.u16 [%0], %1;" ::"l"(op16), "h"((uint16_t)pack2(r, 0.f)) : "memory");
    }
}

__device__ float g_fb[NQ + NQ + FF];
__device__ __forceinline__ float ldbf(const uint16_t* p, size_t i) { return __uint_as_float((uint32_t)p[i] << 16); }
__device__ float fb_block_reduce(float v, bool is_max, float* sh) {
    for (int o = 16; o; o >>= 1) { const float u = shx(v, o); v = is_max ? fmaxf(v, u) : v + u; }
    __syncthreads();
    if ((threadIdx.x & 31) == 0) sh[threadIdx.x >> 5] = v;
    __syncthreads();
    v = sh[0];
    for (int i = 1; i < (int)blockDim.x / 32; i++) v = is_max ? fmaxf(v, sh[i]) : v + sh[i];
    return v;
}
__global__ void fb_proj(const uint16_t* x, const uint16_t* wq, const uint16_t* wg, const uint16_t* wu) {
    __shared__ float xn[D_MODEL], sh[8];
    float a = 0.f;
    for (int i = threadIdx.x; i < D_MODEL; i += 128) a += ldbf(x, i);
    const float mean = fb_block_reduce(a, false, sh) / D_MODEL;
    a = 0.f;
    for (int i = threadIdx.x; i < D_MODEL; i += 128) { const float d = ldbf(x, i) - mean; a += d * d; }
    const float sd = bfr(sqrtf(bfr(bfr(fb_block_reduce(a, false, sh) / D_MODEL) + 1e-5f)));
    for (int i = threadIdx.x; i < D_MODEL; i += 128) xn[i] = bfr(bfr(ldbf(x, i) - bfr(mean)) / sd);
    __syncthreads();
    const int c = blockIdx.x * 128 + threadIdx.x;
    if (c < NQ) {
        float q = 0.f;
        for (int r = 0; r < D_MODEL; r++) q = fmaf(xn[r], ldbf(wq, (size_t)r * NQ + c), q);
        g_fb[c] = bfr(q);
    } else {
        float g = 0.f, u = 0.f;
        for (int r = 0; r < D_MODEL; r++) { g = fmaf(xn[r], ldbf(wg, (size_t)r * FF + c - NQ), g); u = fmaf(xn[r], ldbf(wu, (size_t)r * FF + c - NQ), u); }
        g = bfr(g); u = bfr(u);
        g_fb[NQ + c] = bfr(bfr(0.5f * g * (1.f + tanhf(0.7978845608028654f * (g + 0.044715f * g * g * g)))) * u);
    }
}
__global__ void fb_attn(const uint16_t* kc, const uint16_t* vc) {
    __shared__ float p[WIN], sh[8];
    const size_t base = ((size_t)(blockIdx.x >> 1) * SK + (SK - WIN)) * 128;
    float m = -INFINITY;
    for (int k = threadIdx.x; k < WIN; k += 128) {
        float a = 0.f;
        for (int d = 0; d < 128; d++) a = fmaf(g_fb[blockIdx.x * 128 + d], ldbf(kc, base + (size_t)k * 128 + d), a);
        p[k] = bfr(bfr(a) * 0.08838834764831845f);
        m = fmaxf(m, p[k]);
    }
    m = fb_block_reduce(m, true, sh);
    float l = 0.f;
    for (int k = threadIdx.x; k < WIN; k += 128) { p[k] = __expf(p[k] - m); l += p[k]; }
    l = fb_block_reduce(l, false, sh);
    float o = 0.f;
    for (int k = 0; k < WIN; k++) o = fmaf(p[k], ldbf(vc, base + (size_t)k * 128 + threadIdx.x), o);
    g_fb[NQ + blockIdx.x * 128 + threadIdx.x] = bfr(o / l);
}
__global__ void fb_out(const uint16_t* x, const uint16_t* wo, const uint16_t* wd, uint16_t* out) {
    __shared__ float sh[8];
    const int c = blockIdx.x;
    float a = 0.f;
    for (int r = threadIdx.x; r < NQ; r += 128) a = fmaf(g_fb[NQ + r], ldbf(wo, (size_t)r * D_MODEL + c), a);
    for (int r = threadIdx.x; r < FF; r += 128) a = fmaf(g_fb[2 * NQ + r], ldbf(wd, (size_t)r * D_MODEL + c), a);
    a = fb_block_reduce(a, false, sh);
    if (threadIdx.x == 0) out[c] = (uint16_t)pack2(a + ldbf(x, c), 0.f);
}

typedef CUresult (*EncodeFn)(CUtensorMap*, CUtensorMapDataType, cuuint32_t, void*, const cuuint64_t*, const cuuint64_t*,
                             const cuuint32_t*, const cuuint32_t*, CUtensorMapInterleave, CUtensorMapSwizzle,
                             CUtensorMapL2promotion, CUtensorMapFloatOOBfill);

void make_map(EncodeFn fn, CUtensorMap* m, const void* p, int inner, int outer, int box_inner, int box_outer, CUtensorMapSwizzle sw) {
    cuuint64_t gd[2] = {(cuuint64_t)inner, (cuuint64_t)outer};
    cuuint64_t gs[1] = {(cuuint64_t)inner * 2};
    cuuint32_t bd[2] = {(cuuint32_t)box_inner, (cuuint32_t)box_outer};
    cuuint32_t es[2] = {1, 1};
    fn(m, CU_TENSOR_MAP_DATA_TYPE_BFLOAT16, 2, const_cast<void*>(p), gd, gs, bd, es, CU_TENSOR_MAP_INTERLEAVE_NONE,
       sw, CU_TENSOR_MAP_L2_PROMOTION_L2_128B, CU_TENSOR_MAP_FLOAT_OOB_FILL_NONE);
}

}

extern "C" void kernel_launch(void* const* d_in, const int* in_sizes, int n_in, void* d_out, int out_size) {
    (void)in_sizes; (void)n_in; (void)out_size;
    static int mode = -1;
    static EncodeFn enc_fn = nullptr;
    static void* scratch = nullptr;
    if (mode < 0) {
        cudaDriverEntryPointQueryResult qr;
        void* fn = nullptr;
        cudaGetDriverEntryPoint("cuTensorMapEncodeTiled", &fn, cudaEnableDefault, &qr);
        enc_fn = (EncodeFn)fn;
        cudaGetSymbolAddress(&scratch, g_scratch);
        int dev = 0, sms = 0, occ = 0;
        cudaGetDevice(&dev);
        cudaDeviceGetAttribute(&sms, cudaDevAttrMultiProcessorCount, dev);
        const bool ok = cudaFuncSetAttribute(fused_decode_kernel, cudaFuncAttributeMaxDynamicSharedMemorySize, SMEM_BYTES) == cudaSuccess &&
                        cudaOccupancyMaxActiveBlocksPerMultiprocessor(&occ, fused_decode_kernel, NTHREADS, SMEM_BYTES) == cudaSuccess;
        mode = ok && enc_fn && scratch && sms * occ >= NCTA;
        (void)cudaGetLastError();
    }
    if (!mode) {
        const uint16_t* const* in = (const uint16_t* const*)d_in;
        fb_proj<<<(NQ + FF) / 128, 128>>>(in[0], in[3], in[6], in[7]);
        fb_attn<<<32, 128>>>(in[1], in[2]);
        fb_out<<<D_MODEL, 128>>>(in[0], in[4], in[8], (uint16_t*)d_out);
        return;
    }
    Maps maps;
    make_map(enc_fn, &maps.m[0], d_in[6], FF, D_MODEL, 32, 144, CU_TENSOR_MAP_SWIZZLE_64B);
    make_map(enc_fn, &maps.m[1], d_in[7], FF, D_MODEL, 32, 144, CU_TENSOR_MAP_SWIZZLE_64B);
    make_map(enc_fn, &maps.m[2], d_in[8], 64, FF * 9, 64, 144, CU_TENSOR_MAP_SWIZZLE_128B);
    make_map(enc_fn, &maps.m[3], d_in[4], 64, NQ * 9, 64, 144, CU_TENSOR_MAP_SWIZZLE_128B);
    make_map(enc_fn, &maps.m[4], d_in[8], D_MODEL, FF, 16, 256, CU_TENSOR_MAP_SWIZZLE_32B);
    make_map(enc_fn, &maps.m[5], d_in[3], NQ, D_MODEL, 32, 144, CU_TENSOR_MAP_SWIZZLE_64B);
    fused_decode_kernel<<<NCTA, NTHREADS, SMEM_BYTES>>>(
        (const uint32_t*)d_in[0], (const uint8_t*)d_in[1], (const uint8_t*)d_in[2],
        (uint16_t*)d_out, (Scratch*)scratch, maps);
}
```

```cpp
#include <cuda_runtime.h>
#include <cuda_bf16.h>
#include <cuda.h>
#include <stdint.h>

namespace {

constexpr int D_MODEL = 576;
constexpr int SK = 65536;
constexpr int WIN = 4096;
constexpr int NQ = 4096;
constexpr int FF = 4608;
constexpr int NMAIN = 128;
constexpr int NCTA = 132;
constexpr int NRED = 36;
constexpr int NTHREADS = 352;
constexpr int PACE_W0 = 20000;
constexpr float PACE_NS = 0.0408f;
constexpr int C_DELAY = 400;
constexpr int DEPTH = 6;
constexpr int QPOLL_FROM = 3, OPOLL_FROM = 18, HPOLL_FROM = 21;
constexpr int NCU = 8;
constexpr int CU0 = NMAIN - NCU;
constexpr int CLINES = (16 + NCU) / 8;
constexpr uint32_t KV_BYTES = 16384;
constexpr uint32_t IT_BYTES = 18432;
constexpr uint32_t WQ_OFF = 176128;
constexpr uint32_t MISC_OFF = 212992;
constexpr uint32_t OFF_FULL = MISC_OFF;
constexpr uint32_t OFF_EMPTY = MISC_OFF + 256;
constexpr uint32_t OFF_XN = MISC_OFF + 512;
constexpr uint32_t OFF_RED = OFF_XN + 1152;
constexpr uint32_t OFF_Q = OFF_RED + 9216;
constexpr uint32_t OFF_S = OFF_Q + 512;
constexpr uint32_t OFF_P = OFF_S + 4096;
constexpr uint32_t OFF_OEX = OFF_P + 2048;
constexpr uint32_t OFF_ML = OFF_OEX + 128;
constexpr uint32_t OFF_EP = OFF_ML + 128;
constexpr uint32_t OFF_HX = OFF_EP + 16;
constexpr uint32_t OFF_FIN = OFF_P;
constexpr uint32_t SMEM_BYTES = OFF_HX + (16 + NCU) * 64;
static_assert(SMEM_BYTES <= 232448, "smem");

constexpr uint32_t SPIN_LIMIT = 1u << 20;

struct Scratch {
    uint4 q[16][64];
    uint32_t opart[16][8][8 * 32];
    uint4 hx[16 + NCU][8];
    uint4 outpart[NRED][NMAIN * 4];
    uint32_t epoch[NCTA][32];
};
__device__ __align__(128) Scratch g_scratch;

struct Maps { CUtensorMap m[6]; };

__device__ __forceinline__ uint32_t gtime32() { uint32_t t; asm volatile("mov.u32 %0, %globaltimer_lo;" : "=r"(t)); return t; }

__device__ __forceinline__ uint32_t s2u(const void* p) { return (uint32_t)__cvta_generic_to_shared(p); }
__device__ __forceinline__ void mbar_init(uint32_t a, uint32_t c) { asm volatile("mbarrier.init.shared::cta.b64 [%0], %1;" ::"r"(a), "r"(c) : "memory"); }
__device__ __forceinline__ void mbar_expect(uint32_t a, uint32_t b) { asm volatile("mbarrier.arrive.expect_tx.shared::cta.b64 _, [%0], %1;" ::"r"(a), "r"(b) : "memory"); }
__device__ __forceinline__ void mbar_wait(uint32_t a) {
    uint32_t ok, n = 0;
    do {
        asm volatile("{\n.reg .pred p;\nmbarrier.try_wait.parity.shared::cta.b64 p, [%1], 0;\nselp.u32 %0, 1, 0, p;\n}" : "=r"(ok) : "r"(a) : "memory");
        if (++n > SPIN_LIMIT) __trap();
    } while (!ok);
}
__device__ __forceinline__ bool mbar_test(uint32_t a) {
    uint32_t ok;
    asm volatile("{\n.reg .pred p;\nmbarrier.test_wait.parity.shared::cta.b64 p, [%1], 0;\nselp.u32 %0, 1, 0, p;\n}" : "=r"(ok) : "r"(a) : "memory");
    return ok;
}
__device__ __forceinline__ uint64_t policy_evict_first() { uint64_t p; asm("createpolicy.fractional.L2::evict_first.b64 %0, 1.0;" : "=l"(p)); return p; }
__device__ __forceinline__ uint64_t policy_evict_normal() { uint64_t p; asm("createpolicy.fractional.L2::evict_normal.b64 %0, 1.0;" : "=l"(p)); return p; }
__device__ __forceinline__ void bulk_ld(uint32_t dst, const void* src, uint32_t bytes, uint32_t bar, uint64_t pol) {
    asm volatile("cp.async.bulk.shared::cluster.global.mbarrier::complete_tx::bytes.L2::cache_hint [%0], [%1], %2, [%3], %4;"
                 ::"r"(dst), "l"(src), "r"(bytes), "r"(bar), "l"(pol) : "memory");
}
__device__ __forceinline__ void tma2d_ld(uint32_t dst, const CUtensorMap* m, int c0, int c1, uint32_t bar, uint64_t pol) {
    asm volatile("cp.async.bulk.tensor.2d.shared::cluster.global.mbarrier::complete_tx::bytes.L2::cache_hint [%0], [%1, {%3, %4}], [%2], %5;"
                 ::"r"(dst), "l"(m), "r"(bar), "r"(c0), "r"(c1), "l"(pol) : "memory");
}
__device__ __forceinline__ uint4 lds128(uint32_t a) { uint4 v; asm volatile("ld.shared.v4.u32 {%0,%1,%2,%3}, [%4];" : "=r"(v.x), "=r"(v.y), "=r"(v.z), "=r"(v.w) : "r"(a) : "memory"); return v; }
__device__ __forceinline__ float4 lds128f(uint32_t a) { float4 v; asm volatile("ld.shared.v4.f32 {%0,%1,%2,%3}, [%4];" : "=f"(v.x), "=f"(v.y), "=f"(v.z), "=f"(v.w) : "r"(a) : "memory"); return v; }
__device__ __forceinline__ uint32_t lds32(uint32_t a) { uint32_t v; asm volatile("ld.shared.u32 %0, [%1];" : "=r"(v) : "r"(a) : "memory"); return v; }
__device__ __forceinline__ float lds32f(uint32_t a) { float v; asm volatile("ld.shared.f32 %0, [%1];" : "=f"(v) : "r"(a) : "memory"); return v; }
__device__ __forceinline__ uint4 ldsm4t(uint32_t a) {
    uint4 v;
    asm volatile("ldmatrix.sync.aligned.m8n8.x4.trans.shared.b16 {%0,%1,%2,%3}, [%4];" : "=r"(v.x), "=r"(v.y), "=r"(v.z), "=r"(v.w) : "r"(a) : "memory");
    return v;
}
__device__ __forceinline__ void mma16(float (&c)[4], uint32_t a0, uint32_t a1, uint32_t a2, uint32_t a3, uint32_t b0, uint32_t b1) {
    asm volatile("mma.sync.aligned.m16n8k16.row.col.f32.bf16.bf16.f32 {%0,%1,%2,%3}, {%4,%5,%6,%7}, {%8,%9}, {%0,%1,%2,%3};"
                 : "+f"(c[0]), "+f"(c[1]), "+f"(c[2]), "+f"(c[3]) : "r"(a0), "r"(a1), "r"(a2), "r"(a3), "r"(b0), "r"(b1));
}
__device__ __forceinline__ void mma8(float (&c)[4], uint32_t a0, uint32_t a1, uint32_t b0) {
    asm volatile("mma.sync.aligned.m16n8k8.row.col.f32.bf16.bf16.f32 {%0,%1,%2,%3}, {%4,%5}, {%6}, {%0,%1,%2,%3};"
                 : "+f"(c[0]), "+f"(c[1]), "+f"(c[2]), "+f"(c[3]) : "r"(a0), "r"(a1), "r"(b0));
}
__device__ __forceinline__ uint32_t ldg_nc32(const void* p) { uint32_t v; asm volatile("ld.global.nc.u32 %0, [%1];" : "=r"(v) : "l"(p)); return v; }
__device__ __forceinline__ uint32_t ld_rlx(const uint32_t* p) { uint32_t v; asm volatile("ld.relaxed.gpu.global.u32 %0, [%1];" : "=r"(v) : "l"(p) : "memory"); return v; }
__device__ __forceinline__ uint4 ld_rlx128(const uint4* p) { uint4 v; asm volatile("ld.relaxed.gpu.global.v4.u32 {%0,%1,%2,%3}, [%4];" : "=r"(v.x), "=r"(v.y), "=r"(v.z), "=r"(v.w) : "l"(p) : "memory"); return v; }
__device__ __forceinline__ void ld_rlx128_p(uint4& v, const uint4* p, uint32_t en) {
    asm volatile("{\n.reg .pred p;\nsetp.ne.u32 p, %5, 0;\n@p ld.relaxed.gpu.global.v4.u32 {%0,%1,%2,%3}, [%4];\n}"
                 : "+r"(v.x), "+r"(v.y), "+r"(v.z), "+r"(v.w) : "l"(p), "r"(en) : "memory");
}
__device__ __forceinline__ void st_rlx64(uint32_t* p, uint32_t a, uint32_t b) { asm volatile("st.relaxed.gpu.global.v2.u32 [%0], {%1,%2};" ::"l"(p), "r"(a), "r"(b) : "memory"); }

__device__ __forceinline__ float bf_lo(uint32_t u) { return __uint_as_float(u << 16); }
__device__ __forceinline__ float bf_hi(uint32_t u) { return __uint_as_float(u & 0xffff0000u); }
__device__ __forceinline__ uint32_t pack2(float lo, float hi) { uint32_t r; asm("cvt.rn.bf16x2.f32 %0, %1, %2;" : "=r"(r) : "f"(hi), "f"(lo)); return r; }
__device__ __forceinline__ float bfr(float v) { return __uint_as_float(pack2(0.f, v)); }
__device__ __forceinline__ float shx(float v, int o) { return __shfl_xor_sync(0xffffffffu, v, o); }
__device__ __forceinline__ uint32_t hi2(uint32_t a, uint32_t b) { return __byte_perm(a, b, 0x7632); }

__device__ __forceinline__ void sts32_p(bool en, uint32_t a, uint32_t v) {
    asm volatile("{\n.reg .pred p;\nsetp.ne.u32 p, %2, 0;\n@p st.shared.u32 [%0], %1;\n}" ::"r"(a), "r"(v), "r"((uint32_t)en) : "memory");
}
__device__ __forceinline__ void sts64_p(bool en, uint32_t a, uint32_t x, uint32_t y) {
    asm volatile("{\n.reg .pred p;\nsetp.ne.u32 p, %3, 0;\n@p st.shared.v2.u32 [%0], {%1,%2};\n}" ::"r"(a), "r"(x), "r"(y), "r"((uint32_t)en) : "memory");
}
__device__ __forceinline__ void st_rlx_p(bool en, uint32_t* p, uint32_t v) {
    asm volatile("{\n.reg .pred p;\nsetp.ne.u32 p, %2, 0;\n@p st.relaxed.gpu.global.u32 [%0], %1;\n}" ::"l"(p), "r"(v), "r"((uint32_t)en) : "memory");
}
__device__ __forceinline__ void mbar_arrive_p(bool en, uint32_t a) {
    asm volatile("{\n.reg .pred p;\nsetp.ne.u32 p, %1, 0;\n@p mbarrier.arrive.shared::cta.b64 _, [%0];\n}" ::"r"(a), "r"((uint32_t)en) : "memory");
}
__device__ __forceinline__ void warp_release(bool en, uint32_t a) {
    __syncwarp();
    mbar_arrive_p(en && (threadIdx.x & 31) == 0, a);
}
__device__ __forceinline__ uint32_t lop_ne(uint32_t a, uint32_t b, uint32_t c) { uint32_t r; asm("lop3.b32 %0, %1, %2, %3, 0x7E;" : "=r"(r) : "r"(a), "r"(b), "r"(c)); return r; }
__device__ __forceinline__ uint32_t stale(const uint4& v, uint32_t tg) { return (lop_ne(v.x, v.y, tg) | lop_ne(v.z, v.w, tg)) & 1u; }
__device__ __forceinline__ float selp(float a, float b, uint32_t c) { float r; asm("{\n.reg .pred p;\nsetp.ne.u32 p, %3, 0;\nselp.f32 %0, %1, %2, p;\n}" : "=f"(r) : "f"(a), "f"(b), "r"(c)); return r; }
__device__ __forceinline__ float sel4(float a0, float a1, float a2, float a3, uint32_t i) { return selp(selp(a3, a2, i & 1), selp(a1, a0, i & 1), i & 2); }
#define F2U __float_as_uint
#define U2F __uint_as_float
#define BAR_COMP(id) asm volatile("bar.sync " #id ", 288;" ::: "memory")
#define ZERO44(A) _Pragma("unroll") for (int i_ = 0; i_ < 4; i_++) { A[i_][0] = 0.f; A[i_][1] = 0.f; A[i_][2] = 0.f; A[i_][3] = 0.f; }

__global__ void __launch_bounds__(NTHREADS, 1)
fused_decode_kernel(const uint32_t* __restrict__ x32, const uint8_t* __restrict__ kc, const uint8_t* __restrict__ vc,
                    uint16_t* __restrict__ out16, Scratch* sc, const __grid_constant__ Maps maps) {
    extern __shared__ __align__(1024) uint8_t smem[];
    const uint32_t sb = s2u(smem);
    const int lane = threadIdx.x & 31, wid = threadIdx.x >> 5;
    const int b = blockIdx.x, h = b >> 3, s = b & 7;
    const bool is_main = b < NMAIN, is_red = b < NRED;
    const uint32_t full = sb + OFF_FULL, empty = sb + OFF_EMPTY;
    const uint32_t bar_q = sb + OFF_FULL + 27 * 8, bar_o = bar_q + 8, bar_h = bar_q + 16;
    const size_t kvoff = ((size_t)h * SK + (SK - WIN) + s * 64) * 256;

    if (threadIdx.x == 0) {
        mbar_init(full, 1);
        if (is_main) {
            mbar_expect(full, KV_BYTES);
            bulk_ld(sb, kc + kvoff, KV_BYTES, full, policy_evict_first());
        }
    }
    if (threadIdx.x == 32 && is_main) {
#pragma unroll
        for (int i = 0; i < 2; i++) {
            mbar_init(full + (25 + i) * 8, 1);
            mbar_expect(full + (25 + i) * 8, IT_BYTES);
            tma2d_ld(sb + WQ_OFF + i * IT_BYTES, &maps.m[5], b * 32, i * 288, full + (25 + i) * 8, policy_evict_normal());
            tma2d_ld(sb + WQ_OFF + i * IT_BYTES + 9216, &maps.m[5], b * 32, i * 288 + 144, full + (25 + i) * 8, policy_evict_normal());
        }
    }
    if (wid == 0) {
        const uint32_t t_start = gtime32() - 150;
        if (lane == 0) {
#pragma unroll
            for (int i = 1; i < 25; i++) mbar_init(full + i * 8, 1);
            mbar_init(bar_q, 33);
            mbar_init(bar_o, 32);
            mbar_init(bar_h, 32);
            const uint32_t cnt = is_main ? 8 : 9;
#pragma unroll
            for (int i = 0; i < 13; i++) mbar_init(empty + i * 8, cnt);
            mbar_init(empty + 13 * 8, 9);
        }
        __syncwarp();
        asm volatile("bar.arrive 15, %0;" ::"n"(NTHREADS) : "memory");
        const int i = lane;
        const int j = is_main ? i - 16 : i & 3;
        const int unit = is_main ? b : NMAIN + (b - NMAIN) * 4 + (i >> 2);
        const uint32_t off = !is_main ? (i % 11) * IT_BYTES : i < 12 ? i * KV_BYTES : i < 16 ? (i - 12) * KV_BYTES : i < 24 ? 65536u + (i - 16) * IT_BYTES : 0u;
        const int dep = is_main ? (i < 10 ? -1 : i < 12 ? 13 : i < 16 ? i - 12 : i < 24 ? min(i - 11, 11) : 12) : i - 11;
        const bool skipd = is_main && b >= CU0;
        const int prev = i == 24 ? 21 : i - DEPTH;
        const uint32_t esc = full + (skipd && i == 22 ? 19 : max(i - 1, 0)) * 8;
        const uint8_t* src = (i < 8 ? kc : vc) + kvoff + (i & 7) * (8 * KV_BYTES);
        const CUtensorMap* mp = &maps.m[j < 4 ? 0 : min(j >> 1, 4)];
        const int c0 = j < 4 ? unit * 32 : j < 8 ? 0 : b * 16;
        const int c1 = j < 4 ? j * 144 : j < 8 ? unit * 288 + (j & 1) * 144 : CU0 * 32;
        const uint32_t dst = sb + off, bar = full + i * 8;
        const uint64_t pol = (j < 0 || (j >= 4 && j < 8)) ? policy_evict_first() : policy_evict_normal();
        const int i0 = is_main ? 1 : 0, i1 = is_red ? 25 : is_main ? 24 : 16;
        const int cum = is_main ? 2 * IT_BYTES + (i < 16 ? i * KV_BYTES : 16 * KV_BYTES + (i - 16) * IT_BYTES) : i * IT_BYTES;
        int t_rel = (int)((float)(cum - PACE_W0 + b * 128) * PACE_NS);
        if (i >= i0 && i < i1) mbar_expect(bar, j < 0 ? KV_BYTES : j == 8 ? CLINES * 8192 : IT_BYTES);
        if (lane >= 27) asm volatile("prefetch.tensormap [%0];" ::"l"(&maps.m[lane - 27]) : "memory");
#pragma unroll 1
        for (int k = i0; k < i1; k++) {
            if (lane == k && !(skipd && (k == 20 || k == 21))) {
                if (prev >= 0) mbar_wait(full + prev * 8);
                if (dep >= 0) mbar_wait(empty + dep * 8);
                if (k == 24) t_rel = (int)(gtime32() - t_start) + C_DELAY;
                while ((int)(gtime32() - t_start) < t_rel && !mbar_test(esc)) {}
                if (j < 0) {
                    bulk_ld(dst, src, KV_BYTES, bar, pol);
                } else {
                    tma2d_ld(dst, mp, c0, c1, bar, pol);
                    if (j < 4) tma2d_ld(dst + 9216, mp + 1, c0, c1, bar, pol);
                    if (j == 8) {
#pragma unroll
                        for (int q = 1; q < CLINES; q++) tma2d_ld(dst + q * 8192, mp, c0, c1 + q * 256, bar, pol);
                    }
                }
            }
            __syncwarp();
        }
        return;
    }
    if (wid == 1) {
        __syncwarp();
        asm volatile("bar.sync 15, %0;" ::"n"(NTHREADS) : "memory");
        if (!is_main) return;
        const uint32_t tg = ~lds32(sb + OFF_EP) & 1u;
        uint32_t n = 0;
        {
            mbar_wait(full + QPOLL_FROM * 8);
            uint4 a, c;
            for (;;) {
                a = ld_rlx128(&sc->q[h][lane * 2]);
                c = ld_rlx128(&sc->q[h][lane * 2 + 1]);
                if (!__any_sync(0xffffffffu, stale(a, tg) | stale(c, tg))) break;
                if (++n > SPIN_LIMIT) __trap();
                __nanosleep(100);
            }
            asm volatile("st.shared.v4.u32 [%0], {%1,%2,%3,%4};" ::"r"(sb + OFF_Q + lane * 16), "r"(hi2(a.x, a.y)), "r"(hi2(a.z, a.w)),
                         "r"(hi2(c.x, c.y)), "r"(hi2(c.z, c.w)) : "memory");
            mbar_arrive_p(true, bar_q);
        }
        {
            const uint32_t* slot = &sc->opart[h][s][lane];
            mbar_wait(full + OPOLL_FROM * 8);
            uint32_t ov[8];
            for (;;) {
                uint32_t bad = 0;
#pragma unroll
                for (int i = 0; i < 8; i++) { ov[i] = ld_rlx(slot + i * 32); bad |= ov[i] ^ tg; }
                if (__all_sync(0xffffffffu, !(bad & 1u))) break;
                if (++n > SPIN_LIMIT) __trap();
                __nanosleep(100);
            }
            float mx[8], M = -INFINITY;
#pragma unroll
            for (int i = 0; i < 8; i++) { mx[i] = U2F(__ballot_sync(0xffffffffu, ov[i] & 2u)); M = fmaxf(M, mx[i]); }
            float o = 0.f, L = 0.f;
#pragma unroll
            for (int i = 0; i < 8; i++) {
                const float e = __expf(mx[i] - M);
                o = fmaf(e, U2F(ov[i] & ~7u), o);
                L = fmaf(e, U2F(__ballot_sync(0xffffffffu, ov[i] & 4u)), L);
            }
            o = __fdividef(o, L);
            sts32_p(true, sb + OFF_OEX + lane * 4, pack2(o, __shfl_down_sync(0xffffffffu, o, 1)));
            mbar_arrive_p(true, bar_o);
        }
        if (is_red) {
            mbar_wait(full + HPOLL_FROM * 8);
            uint4 hv[2 * CLINES];
            for (;;) {
                uint32_t bad = 0;
#pragma unroll
                for (int i = 0; i < 2 * CLINES; i++) { hv[i] = ld_rlx128(&sc->hx[0][0] + i * 32 + lane); bad |= stale(hv[i], tg); }
                if (!__any_sync(0xffffffffu, bad)) break;
                if (++n > SPIN_LIMIT) __trap();
                __nanosleep(100);
            }
#pragma unroll
            for (int i = 0; i < 2 * CLINES; i++) sts64_p(true, sb + OFF_HX + i * 256 + lane * 8, hi2(hv[i].x, hv[i].y), hi2(hv[i].z, hv[i].w));
            mbar_arrive_p(true, bar_h);
        }
        return;
    }

    const int w = wid - 2, t = threadIdx.x - 64;
    const int g = lane >> 2, tq = lane & 3;
    float xres;
    {
        const uint32_t xr = ldg_nc32(x32 + (is_red ? b : 0) * 8 + (lane >> 1 & 7));
        xres = (lane & 1) ? bf_hi(xr) : bf_lo(xr);
        uint32_t xa[9];
#pragma unroll
        for (int i = 0; i < 9; i++) xa[i] = ldg_nc32(x32 + i * 32 + lane);
        const uint32_t xmine = ldg_nc32(x32 + t);
        if (t == 0) {
            const uint32_t e = sc->epoch[b][0];
            sc->epoch[b][0] = e + 1;
            sts32_p(true, sb + OFF_EP, e);
        }
        float sum = 0.f;
#pragma unroll
        for (int i = 0; i < 9; i++) sum += bf_lo(xa[i]) + bf_hi(xa[i]);
#pragma unroll
        for (int o = 16; o; o >>= 1) sum += shx(sum, o);
        const float mean = sum * (1.0f / D_MODEL);
        float sq = 0.f;
#pragma unroll
        for (int i = 0; i < 9; i++) { float a = bf_lo(xa[i]) - mean, c = bf_hi(xa[i]) - mean; sq = fmaf(a, a, fmaf(c, c, sq)); }
#pragma unroll
        for (int o = 16; o; o >>= 1) sq += shx(sq, o);
        const float m_bf = bfr(mean);
        const float sd = bfr(sqrtf(bfr(bfr(sq * (1.0f / D_MODEL)) + 1e-5f)));
        sts32_p(true, sb + OFF_XN + t * 4, pack2(bfr(bf_lo(xmine) - m_bf) / sd, bfr(bf_hi(xmine) - m_bf) / sd));
        asm volatile("bar.sync 15, %0;" ::"n"(NTHREADS) : "memory");
    }

    const uint32_t ep = lds32(sb + OFF_EP), tg = ~ep & 1u;
    const int lrow = (lane >> 4) * 8 + (lane & 7), lc = lane >> 3 & 1;
    const uint32_t gu0 = sb + (w * 16 + lrow) * 64 + (lc ^ (lrow >> 1 & 3)) * 16;
    const uint32_t xaddr = sb + OFF_XN + w * 32 + tq * 4;

    auto col_item = [&](float (&ga)[4][4], uint32_t off, uint32_t bar, int ra, int rb) {
        const uint32_t xA = xaddr + ra * 288, xB = xaddr + rb * 288;
        const uint32_t b0 = lds32(xA), b1 = lds32(xA + 16), b2 = lds32(xB), b3 = lds32(xB + 16);
        mbar_wait(bar);
#pragma unroll
        for (int i = 0; i < 4; i++) {
            const uint4 a = ldsm4t((gu0 ^ ((i & 1) * 32)) + off + (i >> 1) * 9216);
            mma16(ga[i], a.x, a.y, a.z, a.w, i < 2 ? b0 : b2, i < 2 ? b1 : b3);
        }
    };
    auto col_reduce = [&](float (&ga)[4][4], uint32_t red, float& gg, float& uu, bool rd) {
        const float v0 = sel4(ga[0][0], ga[1][0], ga[2][0], ga[3][0], tq), v1 = sel4(ga[0][2], ga[1][2], ga[2][2], ga[3][2], tq);
        sts32_p(true, red + w * 256 + tq * 64 + g * 4, F2U(v0));
        sts32_p(true, red + w * 256 + tq * 64 + g * 4 + 32, F2U(v1));
        BAR_COMP(3);
        gg = 0.f; uu = 0.f;
        if (rd) {
#pragma unroll
            for (int k = 0; k < 9; k++) { gg += lds32f(red + k * 256 + lane * 4); uu += lds32f(red + k * 256 + 128 + lane * 4); }
        }
    };
    auto geglu = [&](float gg, float uu) {
        gg = bfr(gg); uu = bfr(uu);
        const float inner = 0.7978845608028654f * (gg + 0.044715f * gg * gg * gg);
        const float hv = bfr(__fdividef(gg, 1.0f + __expf(-2.0f * inner))) * uu;
        return pack2(hv, __shfl_down_sync(0xffffffffu, hv, 1));
    };

    if (!is_main) {
        int it = 0;
        uint32_t off = 0;
#pragma unroll 1
        for (int u = 0; u < 4; u++) {
            float ga[4][4], gg, uu;
            ZERO44(ga)
#pragma unroll 1
            for (int j = 0; j < 4; j++) {
                col_item(ga, off, full + it * 8, j, j);
                warp_release(it < 5, empty + it * 8);
                it++; off = off == 10 * IT_BYTES ? 0u : off + IT_BYTES;
            }
            col_reduce(ga, sb + OFF_RED + (u & 1) * 2304, gg, uu, w == 8);
            const uint32_t hp = geglu(gg, uu);
            st_rlx_p(w == 8, reinterpret_cast<uint32_t*>(&sc->hx[NCU + (b - NMAIN) * 4 + u][0]) + (lane >> 1 & 3) * 8 + (lane >> 3) * 2 + (lane & 1), hp << 16 | tg);
        }
        return;
    }

    uint32_t* outp = reinterpret_cast<uint32_t*>(__shfl_sync(0xffffffffu, reinterpret_cast<unsigned long long>(
                         reinterpret_cast<uint32_t*>(&sc->outpart[w * 4 + tq][b * 4]) + g * 2), lane));
    const int redw = __shfl_sync(0xffffffffu, is_red ? w : -1, lane);
    st_rlx64(outp, ep, ep);
    st_rlx_p(w < 8, &sc->opart[h][w & 7][s * 32 + lane], ep);
    st_rlx_p(w == 8, reinterpret_cast<uint32_t*>(&sc->q[h][s * 8]) + lane, ep);
    st_rlx_p(w == 8 && b >= CU0, reinterpret_cast<uint32_t*>(&sc->hx[max(b - CU0, 0)][0]) + lane, ep);
    float ga[4][4], gg, uu;
    ZERO44(ga)
    col_item(ga, WQ_OFF, full + 25 * 8, 0, 1);
    col_item(ga, WQ_OFF + IT_BYTES, full + 26 * 8, 2, 3);
    warp_release(true, empty + 13 * 8);
    col_reduce(ga, sb + OFF_RED, gg, uu, w == 8);
    st_rlx_p(w == 8, reinterpret_cast<uint32_t*>(&sc->q[h][s * 8]) + lane, pack2(0.f, gg + uu) | tg);
    warp_release(w == 8, bar_q);
    if (w < 8) {
        mbar_wait(bar_q);
        uint4 qf[4];
#pragma unroll
        for (int j = 0; j < 4; j++) qf[j] = lds128(sb + OFF_Q + (g & 1) * 256 + ((j ^ (g >> 1 & 1)) * 4 + tq) * 16);
        const uint32_t koff = sb + (w * 8 + g) * 256 + tq * 16;
        const uint32_t kx = (g & 1) * 64;
        const uint32_t sw = sb + OFF_S + w * 512, pw = sb + OFF_P + w * 256;
        float m = -INFINITY;
#pragma unroll 2
        for (int c = 0; c < 8; c++) {
            mbar_wait(full + c * 8);
            uint4 kv[4];
#pragma unroll
            for (int j = 0; j < 4; j++) kv[j] = lds128(koff + c * KV_BYTES + ((j * 64) ^ kx));
            float c0[4] = {0.f, 0.f, 0.f, 0.f}, c1[4] = {0.f, 0.f, 0.f, 0.f};
#pragma unroll
            for (int j = 0; j < 4; j++) {
                mma16(c0, qf[j].x, qf[j].x, qf[j].y, qf[j].y, kv[j].x, kv[j].y);
                mma16(c1, qf[j].z, qf[j].z, qf[j].w, qf[j].w, kv[j].z, kv[j].w);
            }
            warp_release(true, empty + c * 8);
            const float raw = (g & 2) ? c0[1] + c1[1] : c0[0] + c1[0];
            const float scv = bfr(bfr(raw) * 0.08838834764831845f);
            m = fmaxf(m, scv);
            sts32_p(g < 4, sw + c * 64 + (g & 1) * 32 + tq * 8 + (g & 2) * 2, F2U(scv));
        }
        m = fmaxf(m, shx(m, 1)); m = fmaxf(m, shx(m, 2)); m = fmaxf(m, shx(m, 8));
        __syncwarp();
        {
            const float mh = __shfl_sync(0xffffffffu, m, (lane & 2) * 2);
            const float4 sv = lds128f(sw + lane * 16);
            const uint32_t p01 = pack2(__expf(sv.x - mh), __expf(sv.y - mh)), p23 = pack2(__expf(sv.z - mh), __expf(sv.w - mh));
            sts64_p(true, pw + lane * 8, p01, p23);
            float l = (bf_lo(p01) + bf_hi(p01)) + (bf_lo(p23) + bf_hi(p23));
            l += shx(l, 1); l += shx(l, 4); l += shx(l, 8); l += shx(l, 16);
            sts64_p((lane & 29) == 0, sb + OFF_ML + (lane >> 1) * 64 + w * 8, F2U(mh), F2U(l));
        }
        __syncwarp();
        float oc[8][4];
#pragma unroll
        for (int i = 0; i < 8; i++) { oc[i][0] = 0.f; oc[i][1] = 0.f; oc[i][2] = 0.f; oc[i][3] = 0.f; }
        const uint32_t voff = sb + (w * 8 + (lane & 7)) * 256;
        const uint32_t vx = ((lane >> 3) ^ (lane & 6)) * 16;
#pragma unroll 1
        for (int c = 0; c < 8; c++) {
            uint32_t pb = lds32(pw + c * 32 + (g & 1) * 16 + tq * 4);
            pb = (g >> 1) == tq ? pb : 0u;
            mbar_wait(full + (8 + c) * 8);
            const uint32_t vb = voff + (c < 4 ? c + 8 : c - 4) * KV_BYTES;
#pragma unroll
            for (int j = 0; j < 4; j++) {
                const uint4 a = ldsm4t(vb + ((j * 64) ^ vx));
                mma8(oc[2 * j], a.x, a.y, pb);
                mma8(oc[2 * j + 1], a.z, a.w, pb);
            }
            warp_release(c < 4 || c == 5, empty + min(8 + c, 12) * 8);
        }
#pragma unroll
        for (int i = 0; i < 8; i += 2)
#pragma unroll
            for (int e = 0; e < 4; e++) oc[i][e] += shx(oc[i + 1][e], 1);
#pragma unroll
        for (int i = 0; i < 8; i += 4)
#pragma unroll
            for (int e = 0; e < 4; e++) {
                oc[i][e] += shx(oc[i + 2][e], 2);
                sts32_p(true, sb + OFF_RED + w * 1024 + (e & 1) * 512 + ((2 * i + (e >> 1)) ^ (2 * tq)) * 32 + g * 4, F2U(oc[i][e]));
            }
    }
    BAR_COMP(2);
    if (w < 8) {
        const uint32_t ml = sb + OFF_ML + (t >> 7) * 64;
        float mm[8], ll[8];
#pragma unroll
        for (int i = 0; i < 4; i++) { float4 a = lds128f(ml + i * 16); mm[2 * i] = a.x; ll[2 * i] = a.y; mm[2 * i + 1] = a.z; ll[2 * i + 1] = a.w; }
        float M = mm[0];
#pragma unroll
        for (int i = 1; i < 8; i++) M = fmaxf(M, mm[i]);
        float o = 0.f, L = 0.f;
#pragma unroll
        for (int i = 0; i < 8; i++) {
            float e = __expf(mm[i] - M);
            o = fmaf(e, lds32f(sb + OFF_RED + i * 1024 + t * 4), o);
            L = fmaf(e, ll[i], L);
        }
        st_rlx_p(true, &sc->opart[h][w][s * 32 + lane], (F2U(o) & ~7u) | (F2U(L) >> lane & 1u) << 2 | (F2U(M) >> lane & 1u) << 1 | tg);
    }
    ZERO44(ga)
#pragma unroll
    for (int j = 0; j < 4; j++) col_item(ga, 65536u + j * IT_BYTES, full + (16 + j) * 8, j, j);
    col_reduce(ga, sb + OFF_S, gg, uu, true);
    const uint32_t hp = geglu(gg, uu);

    float acc[4][4];
    ZERO44(acc)
    uint32_t rw[4];
#pragma unroll
    for (int i = 0; i < 4; i++) rw[i] = __shfl_sync(0xffffffffu, sb + (lrow * 9 + w) * 128 + ((i * 32) ^ ((lc ^ ((lrow + w) & 7)) * 16)), lane);
    auto row_item = [&](uint32_t off, uint32_t bar, uint32_t cp, int r0) {
        const uint32_t b0 = __shfl_sync(0xffffffffu, cp, r0 + tq * 2), b1 = __shfl_sync(0xffffffffu, cp, r0 + tq * 2 + 8);
        mbar_wait(bar);
#pragma unroll
        for (int i = 0; i < 4; i++) {
            const uint4 a = ldsm4t(rw[i] + off);
            mma16(acc[i], a.x, a.y, a.z, a.w, b0, b1);
        }
    };
    if (b < CU0) {
        row_item(65536u + 4 * IT_BYTES, full + 20 * 8, hp, 0);
        row_item(65536u + 5 * IT_BYTES, full + 21 * 8, hp, 16);
    } else {
        st_rlx_p(w == 8, reinterpret_cast<uint32_t*>(&sc->hx[b - CU0][0]) + (lane >> 1 & 3) * 8 + (lane >> 3) * 2 + (lane & 1), hp << 16 | tg);
    }
    const uint4* slot = &sc->outpart[is_red ? b : 0][t & 255];
    uint32_t l4 = lane & 4, l8 = lane & 8;
    uint32_t fin_st = sb + OFF_FIN + (tq * 2 + (lane >> 2 & 1) + (lane & 8)) * 80 + w * 4;
    mbar_wait(bar_o);
    const uint32_t op = lds32(sb + OFF_OEX + lane * 4);
    row_item(65536u + 6 * IT_BYTES, full + 22 * 8, op, 0);
    row_item(65536u + 7 * IT_BYTES, full + 23 * 8, op, 16);
    {
        const float v0 = sel4(acc[0][0], acc[1][0], acc[2][0], acc[3][0], tq), v1 = sel4(acc[0][2], acc[1][2], acc[2][2], acc[3][2], tq);
        st_rlx64(outp, (F2U(v0) & ~1u) | tg, (F2U(v1) & ~1u) | tg);
    }
    if (redw < 0) return;
    if (redw < 8) {
        uint4 fa = make_uint4(ep, ep, ep, ep), fb = fa;
        {
            float c0[4] = {0.f, 0.f, 0.f, 0.f}, c1[4] = {0.f, 0.f, 0.f, 0.f};
            const uint32_t cb = sb + (w * (32 * CLINES) + lrow) * 32 + (lc ^ (lrow >> 2 & 1)) * 16;
            mbar_wait(bar_h);
            uint4 hb[CLINES];
#pragma unroll
            for (int i = 0; i < CLINES; i++) hb[i] = lds128(sb + OFF_HX + (w * CLINES + i) * 64 + tq * 16);
            mbar_wait(full + 24 * 8);
#pragma unroll
            for (int i = 0; i < CLINES; i++) {
                const uint4 a = ldsm4t(cb + i * 1024), e = ldsm4t(cb + i * 1024 + 512);
                mma16(c0, a.x, a.y, a.z, a.w, hb[i].x, hb[i].y);
                mma16(c1, e.x, e.y, e.z, e.w, hb[i].z, hb[i].w);
            }
            sts32_p(tq < 2, sb + OFF_FIN + (g + tq * 8) * 80 + 32 + w * 4, F2U(selp(c0[2] + c1[2], c0[0] + c1[0], tq)));
        }
        for (uint32_t n = 0;; n++) {
            const uint32_t sa = stale(fa, tg), sb2 = stale(fb, tg);
            if (!(sa | sb2)) break;
            ld_rlx128_p(fa, slot, sa);
            ld_rlx128_p(fb, slot + 256, sb2);
            if (n > SPIN_LIMIT) __trap();
        }
        __syncwarp();
        const float x0 = U2F(fa.x & ~1u) + U2F(fb.x & ~1u), x1 = U2F(fa.y & ~1u) + U2F(fb.y & ~1u);
        const float x2 = U2F(fa.z & ~1u) + U2F(fb.z & ~1u), x3 = U2F(fa.w & ~1u) + U2F(fb.w & ~1u);
        const float k0 = selp(x2, x0, l4) + shx(selp(x0, x2, l4), 4);
        const float k1 = selp(x3, x1, l4) + shx(selp(x1, x3, l4), 4);
        float k = selp(k1, k0, l8) + shx(selp(k0, k1, l8), 8);
        k += shx(k, 16);
        sts32_p(true, fin_st, F2U(k));
        asm volatile("bar.arrive 4, 288;" ::: "memory");
    } else {
        const uint32_t fa_ = __shfl_sync(0xffffffffu, sb + OFF_FIN + (lane & 15) * 80, lane);
        uint16_t* op16 = reinterpret_cast<uint16_t*>(__shfl_sync(0xffffffffu, reinterpret_cast<unsigned long long>(out16 + b * 16 + (lane & 15)), lane));
        asm volatile("bar.sync 4, 288;" ::: "memory");
        const float4 p0 = lds128f(fa_), p1 = lds128f(fa_ + 16), p2 = lds128f(fa_ + 32), p3 = lds128f(fa_ + 48);
        const float r = ((((p0.x + p0.y) + (p0.z + p0.w)) + ((p1.x + p1.y) + (p1.z + p1.w))) +
                         (((p2.x + p2.y) + (p2.z + p2.w)) + ((p3.x + p3.y) + (p3.z + p3.w)))) + xres;
        if (lane < 16) asm volatile("st.global.u16 [%0], %1;" ::"l"(op16), "h"((uint16_t)pack2(r, 0.f)) : "memory");
    }
}

__device__ float g_fb[NQ + NQ + FF];
__device__ __forceinline__ float ldbf(const uint16_t* p, size_t i) { return __uint_as_float((uint32_t)p[i] << 16); }
__device__ float fb_block_reduce(float v, bool is_max, float* sh) {
    for (int o = 16; o; o >>= 1) { const float u = shx(v, o); v = is_max ? fmaxf(v, u) : v + u; }
    __syncthreads();
    if ((threadIdx.x & 31) == 0) sh[threadIdx.x >> 5] = v;
    __syncthreads();
    v = sh[0];
    for (int i = 1; i < (int)blockDim.x / 32; i++) v = is_max ? fmaxf(v, sh[i]) : v + sh[i];
    return v;
}
__global__ void fb_proj(const uint16_t* x, const uint16_t* wq, const uint16_t* wg, const uint16_t* wu) {
    __shared__ float xn[D_MODEL], sh[8];
    float a = 0.f;
    for (int i = threadIdx.x; i < D_MODEL; i += 128) a += ldbf(x, i);
    const float mean = fb_block_reduce(a, false, sh) / D_MODEL;
    a = 0.f;
    for (int i = threadIdx.x; i < D_MODEL; i += 128) { const float d = ldbf(x, i) - mean; a += d * d; }
    const float sd = bfr(sqrtf(bfr(bfr(fb_block_reduce(a, false, sh) / D_MODEL) + 1e-5f)));
    for (int i = threadIdx.x; i < D_MODEL; i += 128) xn[i] = bfr(bfr(ldbf(x, i) - bfr(mean)) / sd);
    __syncthreads();
    const int c = blockIdx.x * 128 + threadIdx.x;
    if (c < NQ) {
        float q = 0.f;
        for (int r = 0; r < D_MODEL; r++) q = fmaf(xn[r], ldbf(wq, (size_t)r * NQ + c), q);
        g_fb[c] = bfr(q);
    } else {
        float g = 0.f, u = 0.f;
        for (int r = 0; r < D_MODEL; r++) { g = fmaf(xn[r], ldbf(wg, (size_t)r * FF + c - NQ), g); u = fmaf(xn[r], ldbf(wu, (size_t)r * FF + c - NQ), u); }
        g = bfr(g); u = bfr(u);
        g_fb[NQ + c] = bfr(bfr(0.5f * g * (1.f + tanhf(0.7978845608028654f * (g + 0.044715f * g * g * g)))) * u);
    }
}
__global__ void fb_attn(const uint16_t* kc, const uint16_t* vc) {
    __shared__ float p[WIN], sh[8];
    const size_t base = ((size_t)(blockIdx.x >> 1) * SK + (SK - WIN)) * 128;
    float m = -INFINITY;
    for (int k = threadIdx.x; k < WIN; k += 128) {
        float a = 0.f;
        for (int d = 0; d < 128; d++) a = fmaf(g_fb[blockIdx.x * 128 + d], ldbf(kc, base + (size_t)k * 128 + d), a);
        p[k] = bfr(bfr(a) * 0.08838834764831845f);
        m = fmaxf(m, p[k]);
    }
    m = fb_block_reduce(m, true, sh);
    float l = 0.f;
    for (int k = threadIdx.x; k < WIN; k += 128) { p[k] = __expf(p[k] - m); l += p[k]; }
    l = fb_block_reduce(l, false, sh);
    float o = 0.f;
    for (int k = 0; k < WIN; k++) o = fmaf(p[k], ldbf(vc, base + (size_t)k * 128 + threadIdx.x), o);
    g_fb[NQ + blockIdx.x * 128 + threadIdx.x] = bfr(o / l);
}
__global__ void fb_out(const uint16_t* x, const uint16_t* wo, const uint16_t* wd, uint16_t* out) {
    __shared__ float sh[8];
    const int c = blockIdx.x;
    float a = 0.f;
    for (int r = threadIdx.x; r < NQ; r += 128) a = fmaf(g_fb[NQ + r], ldbf(wo, (size_t)r * D_MODEL + c), a);
    for (int r = threadIdx.x; r < FF; r += 128) a = fmaf(g_fb[2 * NQ + r], ldbf(wd, (size_t)r * D_MODEL + c), a);
    a = fb_block_reduce(a, false, sh);
    if (threadIdx.x == 0) out[c] = (uint16_t)pack2(a + ldbf(x, c), 0.f);
}

typedef CUresult (*EncodeFn)(CUtensorMap*, CUtensorMapDataType, cuuint32_t, void*, const cuuint64_t*, const cuuint64_t*,
                             const cuuint32_t*, const cuuint32_t*, CUtensorMapInterleave, CUtensorMapSwizzle,
                             CUtensorMapL2promotion, CUtensorMapFloatOOBfill);

void make_map(EncodeFn fn, CUtensorMap* m, const void* p, int inner, int outer, int box_inner, int box_outer, CUtensorMapSwizzle sw) {
    cuuint64_t gd[2] = {(cuuint64_t)inner, (cuuint64_t)outer};
    cuuint64_t gs[1] = {(cuuint64_t)inner * 2};
    cuuint32_t bd[2] = {(cuuint32_t)box_inner, (cuuint32_t)box_outer};
    cuuint32_t es[2] = {1, 1};
    fn(m, CU_TENSOR_MAP_DATA_TYPE_BFLOAT16, 2, const_cast<void*>(p), gd, gs, bd, es, CU_TENSOR_MAP_INTERLEAVE_NONE,
       sw, CU_TENSOR_MAP_L2_PROMOTION_L2_128B, CU_TENSOR_MAP_FLOAT_OOB_FILL_NONE);
}

}

extern "C" void kernel_launch(void* const* d_in, const int* in_sizes, int n_in, void* d_out, int out_size) {
    (void)in_sizes; (void)n_in; (void)out_size;
    static int mode = -1;
    static EncodeFn enc_fn = nullptr;
    static void* scratch = nullptr;
    if (mode < 0) {
        cudaDriverEntryPointQueryResult qr;
        void* fn = nullptr;
        cudaGetDriverEntryPoint("cuTensorMapEncodeTiled", &fn, cudaEnableDefault, &qr);
        enc_fn = (EncodeFn)fn;
        cudaGetSymbolAddress(&scratch, g_scratch);
        int dev = 0, sms = 0, occ = 0;
        cudaGetDevice(&dev);
        cudaDeviceGetAttribute(&sms, cudaDevAttrMultiProcessorCount, dev);
        const bool ok = cudaFuncSetAttribute(fused_decode_kernel, cudaFuncAttributeMaxDynamicSharedMemorySize, SMEM_BYTES) == cudaSuccess &&
                        cudaOccupancyMaxActiveBlocksPerMultiprocessor(&occ, fused_decode_kernel, NTHREADS, SMEM_BYTES) == cudaSuccess;
        mode = ok && enc_fn && scratch && sms * occ >= NCTA;
        (void)cudaGetLastError();
    }
    if (!mode) {
        const uint16_t* const* in = (const uint16_t* const*)d_in;
        fb_proj<<<(NQ + FF) / 128, 128>>>(in[0], in[3], in[6], in[7]);
        fb_attn<<<32, 128>>>(in[1], in[2]);
        fb_out<<<D_MODEL, 128>>>(in[0], in[4], in[8], (uint16_t*)d_out);
        return;
    }
    Maps maps;
    make_map(enc_fn, &maps.m[0], d_in[6], FF, D_MODEL, 32, 144, CU_TENSOR_MAP_SWIZZLE_64B);
    make_map(enc_fn, &maps.m[1], d_in[7], FF, D_MODEL, 32, 144, CU_TENSOR_MAP_SWIZZLE_64B);
    make_map(enc_fn, &maps.m[2], d_in[8], 64, FF * 9, 64, 144, CU_TENSOR_MAP_SWIZZLE_128B);
    make_map(enc_fn, &maps.m[3], d_in[4], 64, NQ * 9, 64, 144, CU_TENSOR_MAP_SWIZZLE_128B);
    make_map(enc_fn, &maps.m[4], d_in[8], D_MODEL, FF, 16, 256, CU_TENSOR_MAP_SWIZZLE_32B);
    make_map(enc_fn, &maps.m[5], d_in[3], NQ, D_MODEL, 32, 144, CU_TENSOR_MAP_SWIZZLE_64B);
    fused_decode_kernel<<<NCTA, NTHREADS, SMEM_BYTES>>>(
        (const uint32_t*)d_in[0], (const uint8_t*)d_in[1], (const uint8_t*)d_in[2],
        (uint16_t*)d_out, (Scratch*)scratch, maps);
}
```
